```python
import torch

def _softmax(x, axis=-1):
    return torch.softmax(x, dim=axis)
def _gelu(x):
    return torch.nn.functional.gelu(x, approximate="tanh")
def _silu(x):
    return torch.nn.functional.silu(x)
def _sigmoid(x):
    return torch.sigmoid(x)
def _layernorm(x, axis=-1, eps=1e-5):
    m = x.mean(dim=axis, keepdim=True)
    v = x.var(dim=axis, keepdim=True, unbiased=False)
    return (x - m) / torch.sqrt(v + eps)
def _scatter_add(tgt, idx, src, axis=0):
    return tgt.clone().index_add_(axis, idx, src)
def _segment_sum(src, seg, n):
    out = torch.zeros((n,) + src.shape[1:], dtype=src.dtype)
    return out.index_add_(0, seg, src)
def _pad(x, pw):
    flat = tuple(v for pair in reversed(pw) for v in pair)
    return torch.nn.functional.pad(x, flat)

kernel_name = 'concat_heads__mha_block_cached__mha_block_cached__near_ridge'

def setup_inputs():

    _w = (lambda a: (lambda t: t.to(torch.bfloat16) if t.is_floating_point() else t)(torch.as_tensor(a)))
    def _A_setup():
        B, Sq, D = 8, 160, 1024
        H, Sk, Dh = 32, 1024, 128
        return {
            "x": _w((lambda *s: torch.randn(*s, dtype=torch.bfloat16) * 0.8)(B, Sq, D)),
            "k_cache": _w((lambda *s: torch.randn(*s, dtype=torch.bfloat16) * 0.8)(B, H, Sk, Dh)),
            "v_cache": _w((lambda *s: torch.randn(*s, dtype=torch.bfloat16) * 0.05)(B, H, Sk, Dh)),
            "wq": _w((lambda *s: torch.randn(*s, dtype=torch.bfloat16) * 0.8)(D, H * Dh) * (D ** -0.5)),
            "wo": _w((lambda *s: torch.randn(*s, dtype=torch.bfloat16) * 0.05)(H * Dh, D) * ((H * Dh) ** -0.5)),
        }
    _A_in = _A_setup()

    def _B_setup():
        B, Sq, D = 8, 160, 1024
        H, Sk, Dh = 32, 1024, 128
        return {
            "x": _w((lambda *s: torch.randn(*s, dtype=torch.bfloat16) * 0.8)(B, Sq, D)),
            "k_cache": _w((lambda *s: torch.randn(*s, dtype=torch.bfloat16) * 0.8)(B, H, Sk, Dh)),
            "v_cache": _w((lambda *s: torch.randn(*s, dtype=torch.bfloat16) * 0.05)(B, H, Sk, Dh)),
            "wq": _w((lambda *s: torch.randn(*s, dtype=torch.bfloat16) * 0.8)(D, H * Dh) * (D ** -0.5)),
            "wo": _w((lambda *s: torch.randn(*s, dtype=torch.bfloat16) * 0.05)(H * Dh, D) * ((H * Dh) ** -0.5)),
        }
    _B_in = _B_setup()

    return {
        "A_x": _A_in["x"],
        "A_k_cache": _A_in["k_cache"],
        "A_v_cache": _A_in["v_cache"],
        "A_wq": _A_in["wq"],
        "A_wo": _A_in["wo"],
        "B_x": _B_in["x"],
        "B_k_cache": _B_in["k_cache"],
        "B_v_cache": _B_in["v_cache"],
        "B_wq": _B_in["wq"],
        "B_wo": _B_in["wo"],
    }

def reference(A_x, A_k_cache, A_v_cache, A_wq, A_wo, B_x, B_k_cache, B_v_cache, B_wq, B_wo):
    def _A_ref(x, k_cache, v_cache, wq, wo):
        B, Sq, D = x.shape
        H, Dh = 32, 128
        q = (lambda x, *d: x.permute(*d))((x @ wq).reshape(B, Sq, H, Dh), 0, 2, 1, 3)
        scores = torch.einsum("bhqd,bhkd->bhqk", q, k_cache) * (Dh ** -0.5)
        p = _softmax(scores, axis=-1)
        o = torch.einsum("bhqk,bhkd->bhqd", p, v_cache)
        return (lambda x, *d: x.permute(*d))(o, 0, 2, 1, 3).reshape(B, Sq, H * Dh) @ wo

    def _B_ref(x, k_cache, v_cache, wq, wo):
        B, Sq, D = x.shape
        H, Dh = 32, 128
        q = (lambda x, *d: x.permute(*d))((x @ wq).reshape(B, Sq, H, Dh), 0, 2, 1, 3)
        scores = torch.einsum("bhqd,bhkd->bhqk", q, k_cache) * (Dh ** -0.5)
        p = _softmax(scores, axis=-1)
        o = torch.einsum("bhqk,bhkd->bhqd", p, v_cache)
        return (lambda x, *d: x.permute(*d))(o, 0, 2, 1, 3).reshape(B, Sq, H * Dh) @ wo

    a = _A_ref(A_x, A_k_cache, A_v_cache, A_wq, A_wo)
    b = _B_ref(B_x, B_k_cache, B_v_cache, B_wq, B_wo)
    return torch.concatenate([a, b], axis=-1)
```

```cpp
#include <cuda_runtime.h>
#include <cuda_bf16.h>
#include <cuda.h>
#include <stdint.h>

namespace {

constexpr int SQ = 160, SK = 1024, NH = 32;
constexpr int NCTA = 128;

constexpr uint32_t sb = 1024;
constexpr uint32_t PR_BYTES = 18432;
constexpr uint32_t SM_Q = 4 * PR_BYTES;
constexpr uint32_t SM_P = SM_Q + 40960;
constexpr uint32_t P_BYTES = 20480;
constexpr uint32_t SM_K = SM_P + 2 * P_BYTES;
constexpr uint32_t SM_V = SM_K + 2 * 16384;
constexpr uint32_t SM_LINV = SM_V + 2 * 16384;
constexpr uint32_t SM_BAR = SM_LINV + 160 * 4;
constexpr uint32_t SM_TOTAL = SM_BAR + 704;
static_assert(SM_V + 2 * 16384 == 12 * PR_BYTES, "Q/P/K/V double as 8 extra projection slots before and after attention");
constexpr uint32_t B_KFULL = SM_BAR + 0;
constexpr uint32_t B_KEMPTY = SM_BAR + 16;
constexpr uint32_t B_VFULL = SM_BAR + 32;
constexpr uint32_t B_VEMPTY = SM_BAR + 48;
constexpr uint32_t B_PFULL = SM_BAR + 64;
constexpr uint32_t B_PEMPTY = SM_BAR + 80;
constexpr uint32_t B_QFULL = SM_BAR + 96;
constexpr uint32_t B_QREADY = SM_BAR + 112;
constexpr uint32_t B_ODONE = SM_BAR + 144;
constexpr uint32_t B_QVIS = SM_BAR + 176;
constexpr uint32_t B_PRFULL = SM_BAR + 208;
constexpr uint32_t B_PREMPTY = SM_BAR + 304;
constexpr uint32_t B_ORDY = SM_BAR + 400;
constexpr uint32_t B_KVGO = SM_BAR + 656;
constexpr uint32_t B_QFREE = SM_BAR + 672;
#define K_START 12
#define V_START 18
#define QS1 3
#define QS2 6
constexpr int PD = 20;

__device__ __forceinline__ void pr_slot(int n, uint32_t& slot, uint32_t& par) {
    if (n >= 28 && n < 224) {
        slot = n & 3;
        par = (n >> 2) & 1;
    } else if (n >= 224) {
        const int m = n - 224, w = m >= 24 ? 2 : (m >= 12 ? 1 : 0);
        slot = m - 12 * w;
        par = (slot < 4 ? w : w + 1) & 1;
    } else if (n >= 4) {
        slot = n & 7;
        par = ((n - 4) >> 3) & 1;
    } else {
        slot = 8 + n;
        par = 0;
    }
}

template <int V> struct IC { static constexpr int value = V; };
template <int N, int I = 0, class F> __device__ __forceinline__ void static_for(F&& f) {
    if constexpr (I < N) {
        f(IC<I>{});
        static_for<N, I + 1>(f);
    }
}

struct Params {
    CUtensorMap k[2], v[2], x[2], wq[2], wo[2], out;
    const __nv_bfloat16* kp[2];
    const __nv_bfloat16* vp[2];
    const __nv_bfloat16* xp[2];
    const __nv_bfloat16* wqp[2];
    int zero;
};

__device__ __align__(1024) unsigned char g_scr[16 * 32 * 40960];
__device__ __align__(128) unsigned int g_flag[16 * 32];
__device__ unsigned int g_epoch[NCTA];

#define TR(role, idx)
#define TRG(role, idx)
#define TR2(role, idx)

__device__ __forceinline__ void mbar_init(uint32_t b, int c) {
    asm volatile("mbarrier.init.shared::cta.b64 [%0], %1;" ::"r"(b), "r"(c));
}
__device__ __forceinline__ void mbar_expect(uint32_t b, int bytes) {
    asm volatile("mbarrier.arrive.expect_tx.shared::cta.b64 _, [%0], %1;" ::"r"(b), "r"(bytes) : "memory");
}
__device__ __forceinline__ void mbar_arrive(uint32_t b) {
    asm volatile("mbarrier.arrive.shared::cta.b64 _, [%0];" ::"r"(b) : "memory");
}
__device__ __forceinline__ void mbar_wait(uint32_t b, uint32_t ph) {
    asm volatile(
        "{\n.reg .pred p;\n.reg .u32 n;\n"
        "mbarrier.try_wait.parity.shared::cta.b64 p, [%0], %1;\n"
        "@p bra D;\n"
        "mov.u32 n, 0;\n"
        "W:\nmbarrier.try_wait.parity.shared::cta.b64 p, [%0], %1;\n"
        "@p bra D;\n"
        "add.u32 n, n, 1;\nsetp.lt.u32 p, n, 33554432;\n@p bra W;\ntrap;\n"
        "D:\n}" ::"r"(b), "r"(ph) : "memory");
}
__device__ __forceinline__ bool mbar_test(uint32_t b, uint32_t ph) {
    uint32_t r;
    asm volatile("{\n.reg .pred p;\nmbarrier.test_wait.parity.shared::cta.b64 p, [%1], %2;\nselp.u32 %0, 1, 0, p;\n}"
                 : "=r"(r) : "r"(b), "r"(ph) : "memory");
    return r != 0;
}
__device__ __forceinline__ void pf3(const CUtensorMap* m, int c0, int c1, int c2) {
    asm volatile("cp.async.bulk.prefetch.tensor.3d.L2.global [%0, {%1, %2, %3}];" ::"l"(m), "r"(c0), "r"(c1), "r"(c2) : "memory");
}
__device__ __forceinline__ void pf3_hint(const CUtensorMap* m, int c0, int c1, int c2, uint64_t pol) {
    asm volatile("cp.async.bulk.prefetch.tensor.3d.L2.global.L2::cache_hint [%0, {%1, %2, %3}], %4;" ::"l"(m), "r"(c0), "r"(c1), "r"(c2), "l"(pol) : "memory");
}
#define WPOL 0
constexpr uint64_t POL_EF = 0x12F0000000000000ull;
__device__ __forceinline__ void pf2(const CUtensorMap* m, int c0, int c1) {
    asm volatile("cp.async.bulk.prefetch.tensor.2d.L2.global [%0, {%1, %2}];" ::"l"(m), "r"(c0), "r"(c1) : "memory");
}
__device__ __forceinline__ void pfb(const void* p, int bytes) {
    asm volatile("cp.async.bulk.prefetch.L2.global [%0], %1;" ::"l"(p), "r"(bytes) : "memory");
}
__device__ __forceinline__ void sts128(uint32_t p, uint32_t a, uint32_t b, uint32_t c, uint32_t d) {
    asm volatile("st.shared.v4.u32 [%0], {%1, %2, %3, %4};" ::"r"(p), "r"(a), "r"(b), "r"(c), "r"(d) : "memory");
}
__device__ __forceinline__ void tma3(uint32_t dst, const CUtensorMap* m, int c0, int c1, int c2, uint32_t bar) {
    asm volatile("cp.async.bulk.tensor.3d.shared::cluster.global.mbarrier::complete_tx::bytes [%0], [%1, {%3, %4, %5}], [%2];"
                 ::"r"(dst), "l"(m), "r"(bar), "r"(c0), "r"(c1), "r"(c2) : "memory");
}
__device__ __forceinline__ void tma3_hint(uint32_t dst, const CUtensorMap* m, int c0, int c1, int c2, uint32_t bar, uint64_t pol) {
    asm volatile("cp.async.bulk.tensor.3d.shared::cluster.global.mbarrier::complete_tx::bytes.L2::cache_hint [%0], [%1, {%3, %4, %5}], [%2], %6;"
                 ::"r"(dst), "l"(m), "r"(bar), "r"(c0), "r"(c1), "r"(c2), "l"(pol) : "memory");
}
__device__ __forceinline__ void tmaw(uint32_t dst, const CUtensorMap* m, int c1, int c2, uint32_t bar) {
    if (WPOL >= 1) tma3_hint(dst, m, 0, c1, c2, bar, POL_EF);
    else tma3(dst, m, 0, c1, c2, bar);
}
__device__ __forceinline__ void pfw(const CUtensorMap* m, int c1, int c2) {
    if (WPOL >= 2) pf3_hint(m, 0, c1, c2, POL_EF);
    else pf3(m, 0, c1, c2);
}
__device__ __forceinline__ void tma2(uint32_t dst, const CUtensorMap* m, int c0, int c1, uint32_t bar) {
    asm volatile("cp.async.bulk.tensor.2d.shared::cluster.global.mbarrier::complete_tx::bytes [%0], [%1, {%3, %4}], [%2];"
                 ::"r"(dst), "l"(m), "r"(bar), "r"(c0), "r"(c1) : "memory");
}
__device__ __forceinline__ void bulk_g2s(uint32_t dst, const void* src, int bytes, uint32_t bar) {
    asm volatile("cp.async.bulk.shared::cluster.global.mbarrier::complete_tx::bytes [%0], [%1], %2, [%3];"
                 ::"r"(dst), "l"(src), "r"(bytes), "r"(bar) : "memory");
}
__device__ __forceinline__ void bulk_s2g(void* dst, uint32_t src, int bytes) {
    asm volatile("cp.async.bulk.global.shared::cta.bulk_group [%0], [%1], %2;" ::"l"(dst), "r"(src), "r"(bytes) : "memory");
}
__device__ __forceinline__ void mbar_arrive4(uint32_t b) {
    asm volatile("mbarrier.arrive.shared::cta.b64 _, [%0], 4;" ::"r"(b) : "memory");
}
__device__ __forceinline__ void tma2_store(const CUtensorMap* m, uint32_t src, int c0, int c1) {
    asm volatile("cp.async.bulk.tensor.2d.global.shared::cta.bulk_group [%0, {%2, %3}], [%1];"
                 ::"l"(m), "r"(src), "r"(c0), "r"(c1) : "memory");
}
__device__ __forceinline__ void wg_fence() { asm volatile("wgmma.fence.sync.aligned;" ::: "memory"); }
__device__ __forceinline__ void wg_commit() { asm volatile("wgmma.commit_group.sync.aligned;" ::: "memory"); }
template <int N> __device__ __forceinline__ void wg_wait() { asm volatile("wgmma.wait_group.sync.aligned %0;" ::"n"(N) : "memory"); }
template <int N> __device__ __forceinline__ void acc_fence(float (&d)[N]) {
#pragma unroll
    for (int i = 0; i < N; i++) asm volatile("" : "+f"(d[i])::"memory");
}
template <uint32_t OFF> __device__ __forceinline__ void sts128i(uint32_t p, uint32_t a, uint32_t b, uint32_t c, uint32_t d) {
    asm volatile("st.shared.v4.u32 [%0+%5], {%1, %2, %3, %4};" ::"r"(p), "r"(a), "r"(b), "r"(c), "r"(d), "n"(OFF) : "memory");
}
template <uint32_t OFF> __device__ __forceinline__ void lds128i(uint32_t p, float* v) {
    asm volatile("ld.shared.v4.f32 {%0, %1, %2, %3}, [%4+%5];" : "=f"(v[0]), "=f"(v[1]), "=f"(v[2]), "=f"(v[3]) : "r"(p), "n"(OFF) : "memory");
}
template <uint32_t LBO, uint32_t SBO, uint32_t SWZ>
__device__ __forceinline__ uint64_t mkdesc(uint32_t addr) {
    uint32_t lo = ((addr & 0x3FFFF) >> 4) | ((LBO >> 4) << 16);
    uint32_t hi = (SBO >> 4) | (SWZ << 30);
    return ((uint64_t)hi << 32) | lo;
}

template <int TA, int TB>
__device__ __forceinline__ void wgmma160(float (&d)[80], uint64_t da, uint64_t db, int scale_d) {
    asm volatile(
        "{\n.reg .pred p;\nsetp.ne.b32 p, %82, 0;\n"
        "wgmma.mma_async.sync.aligned.m64n160k16.f32.bf16.bf16 "
        "{%0, %1, %2, %3, %4, %5, %6, %7, %8, %9, %10, %11, %12, %13, %14, %15, %16, %17, %18, %19, "
        "%20, %21, %22, %23, %24, %25, %26, %27, %28, %29, %30, %31, %32, %33, %34, %35, %36, %37, %38, %39, "
        "%40, %41, %42, %43, %44, %45, %46, %47, %48, %49, %50, %51, %52, %53, %54, %55, %56, %57, %58, %59, "
        "%60, %61, %62, %63, %64, %65, %66, %67, %68, %69, %70, %71, %72, %73, %74, %75, %76, %77, %78, %79}, "
        "%80, %81, p, 1, 1, %83, %84;\n}\n"
        : "+f"(d[0]), "+f"(d[1]), "+f"(d[2]), "+f"(d[3]), "+f"(d[4]), "+f"(d[5]), "+f"(d[6]), "+f"(d[7]),
          "+f"(d[8]), "+f"(d[9]), "+f"(d[10]), "+f"(d[11]), "+f"(d[12]), "+f"(d[13]), "+f"(d[14]), "+f"(d[15]),
          "+f"(d[16]), "+f"(d[17]), "+f"(d[18]), "+f"(d[19]), "+f"(d[20]), "+f"(d[21]), "+f"(d[22]), "+f"(d[23]),
          "+f"(d[24]), "+f"(d[25]), "+f"(d[26]), "+f"(d[27]), "+f"(d[28]), "+f"(d[29]), "+f"(d[30]), "+f"(d[31]),
          "+f"(d[32]), "+f"(d[33]), "+f"(d[34]), "+f"(d[35]), "+f"(d[36]), "+f"(d[37]), "+f"(d[38]), "+f"(d[39]),
          "+f"(d[40]), "+f"(d[41]), "+f"(d[42]), "+f"(d[43]), "+f"(d[44]), "+f"(d[45]), "+f"(d[46]), "+f"(d[47]),
          "+f"(d[48]), "+f"(d[49]), "+f"(d[50]), "+f"(d[51]), "+f"(d[52]), "+f"(d[53]), "+f"(d[54]), "+f"(d[55]),
          "+f"(d[56]), "+f"(d[57]), "+f"(d[58]), "+f"(d[59]), "+f"(d[60]), "+f"(d[61]), "+f"(d[62]), "+f"(d[63]),
          "+f"(d[64]), "+f"(d[65]), "+f"(d[66]), "+f"(d[67]), "+f"(d[68]), "+f"(d[69]), "+f"(d[70]), "+f"(d[71]),
          "+f"(d[72]), "+f"(d[73]), "+f"(d[74]), "+f"(d[75]), "+f"(d[76]), "+f"(d[77]), "+f"(d[78]), "+f"(d[79])
        : "l"(da), "l"(db), "r"(scale_d), "n"(TA), "n"(TB));
}
template <int TA, int TB>
__device__ __forceinline__ void wgmma80(float (&d)[40], uint64_t da, uint64_t db, int scale_d) {
    asm volatile(
        "{\n.reg .pred p;\nsetp.ne.b32 p, %42, 0;\n"
        "wgmma.mma_async.sync.aligned.m64n80k16.f32.bf16.bf16 "
        "{%0, %1, %2, %3, %4, %5, %6, %7, %8, %9, %10, %11, %12, %13, %14, %15, %16, %17, %18, %19, "
        "%20, %21, %22, %23, %24, %25, %26, %27, %28, %29, %30, %31, %32, %33, %34, %35, %36, %37, %38, %39}, "
        "%40, %41, p, 1, 1, %43, %44;\n}\n"
        : "+f"(d[0]), "+f"(d[1]), "+f"(d[2]), "+f"(d[3]), "+f"(d[4]), "+f"(d[5]), "+f"(d[6]), "+f"(d[7]),
          "+f"(d[8]), "+f"(d[9]), "+f"(d[10]), "+f"(d[11]), "+f"(d[12]), "+f"(d[13]), "+f"(d[14]), "+f"(d[15]),
          "+f"(d[16]), "+f"(d[17]), "+f"(d[18]), "+f"(d[19]), "+f"(d[20]), "+f"(d[21]), "+f"(d[22]), "+f"(d[23]),
          "+f"(d[24]), "+f"(d[25]), "+f"(d[26]), "+f"(d[27]), "+f"(d[28]), "+f"(d[29]), "+f"(d[30]), "+f"(d[31]),
          "+f"(d[32]), "+f"(d[33]), "+f"(d[34]), "+f"(d[35]), "+f"(d[36]), "+f"(d[37]), "+f"(d[38]), "+f"(d[39])
        : "l"(da), "l"(db), "r"(scale_d), "n"(TA), "n"(TB));
}
__device__ __forceinline__ uint32_t pack_bf16(float lo, float hi) {
    uint32_t r;
    asm("cvt.rn.bf16x2.f32 %0, %1, %2;" : "=r"(r) : "f"(hi), "f"(lo));
    return r;
}
__device__ __forceinline__ uint32_t hadd2(uint32_t a, uint32_t b) {
    uint32_t r;
    asm("add.rn.bf16x2 %0, %1, %2;" : "=r"(r) : "r"(a), "r"(b));
    return r;
}
#define PVW 3
__device__ __forceinline__ float ex2(float x) {
    float r;
    asm("ex2.approx.ftz.f32 %0, %1;" : "=f"(r) : "f"(x));
    return r;
}
__device__ __forceinline__ void stsm4t(uint32_t addr, uint32_t a, uint32_t b, uint32_t c, uint32_t d) {
    asm volatile("stmatrix.sync.aligned.m8n8.x4.trans.shared.b16 [%0], {%1, %2, %3, %4};"
                 ::"r"(addr), "r"(a), "r"(b), "r"(c), "r"(d) : "memory");
}
__device__ __forceinline__ void stg128(void* p, uint32_t a, uint32_t b, uint32_t c, uint32_t d) {
    asm volatile("st.global.v4.u32 [%0], {%1, %2, %3, %4};" ::"l"(p), "r"(a), "r"(b), "r"(c), "r"(d) : "memory");
}

template <int W, int TB, uint32_t BSTEP>
__device__ __forceinline__ void proj_stage(float (&a0)[80], float (&a1)[80], uint64_t da, uint64_t db, int acc, uint32_t rel,
                                           bool leader) {
    wg_wait<W - 1>();
    if (W == 1 && leader && rel) mbar_arrive(rel);
    wg_fence();
    wgmma160<1, TB>(a0, da, db, acc);
    wg_commit();
    wg_wait<W - 1>();
    if (W == 2 && leader && rel) mbar_arrive(rel);
    wgmma160<1, TB>(a1, da + (4096 >> 4), db, acc);
    wg_commit();
    wg_wait<W - 1>();
    if (W == 3 && leader && rel) mbar_arrive(rel);
    wgmma160<1, TB>(a0, da + (2048 >> 4), db + (BSTEP >> 4), 1);
    wg_commit();
    wg_wait<W - 1>();
    if (W == 4 && leader && rel) mbar_arrive(rel);
    wgmma160<1, TB>(a1, da + (6144 >> 4), db + (BSTEP >> 4), 1);
    wg_commit();
}
#define PW 2
#define PWD 4

constexpr float QSCALE = 0.08838834764831845f * 1.4426950408889634f;

__device__ __noinline__ void slow_head(const __nv_bfloat16* xp, const __nv_bfloat16* wp, const __nv_bfloat16* kp,
                                       const __nv_bfloat16* vp, unsigned char* os, int warp, int lane) {
    for (int qn = warp; qn < SQ; qn += 4) {
        float q[4] = {0.f, 0.f, 0.f, 0.f}, o[4] = {0.f, 0.f, 0.f, 0.f};
#pragma unroll 8
        for (int k = 0; k < 1024; k++) {
            const float xv = __bfloat162float(xp[qn * 1024 + k]);
            const uint2 w = __ldg(reinterpret_cast<const uint2*>(wp + (size_t)k * 4096 + 4 * lane));
            q[0] += xv * __uint_as_float(w.x << 16);
            q[1] += xv * __uint_as_float(w.x & 0xffff0000u);
            q[2] += xv * __uint_as_float(w.y << 16);
            q[3] += xv * __uint_as_float(w.y & 0xffff0000u);
        }
#pragma unroll
        for (int u = 0; u < 4; u++) q[u] = __uint_as_float(pack_bf16(q[u], 0.f) << 16) * QSCALE;
        float m = -INFINITY, l = 0.f;
        for (int key = 0; key < SK; key += 4) {
            float s[4];
            uint2 vv[4];
#pragma unroll
            for (int u = 0; u < 4; u++) {
                const uint2 kk = __ldg(reinterpret_cast<const uint2*>(kp + (key + u) * 128 + 4 * lane));
                vv[u] = __ldg(reinterpret_cast<const uint2*>(vp + (key + u) * 128 + 4 * lane));
                s[u] = q[0] * __uint_as_float(kk.x << 16) + q[1] * __uint_as_float(kk.x & 0xffff0000u) +
                       q[2] * __uint_as_float(kk.y << 16) + q[3] * __uint_as_float(kk.y & 0xffff0000u);
            }
#pragma unroll
            for (int off = 16; off; off >>= 1) {
#pragma unroll
                for (int u = 0; u < 4; u++) s[u] += __shfl_xor_sync(0xffffffffu, s[u], off);
            }
            const float mn = fmaxf(fmaxf(m, fmaxf(s[0], s[1])), fmaxf(s[2], s[3]));
            const float mref = (mn == -INFINITY) ? 0.f : mn;
            const float corr = exp2f(m - mref);
            m = mn;
            l *= corr;
            o[0] *= corr; o[1] *= corr; o[2] *= corr; o[3] *= corr;
#pragma unroll
            for (int u = 0; u < 4; u++) {
                const float pw = exp2f(s[u] - mref);
                l += pw;
                o[0] += pw * __uint_as_float(vv[u].x << 16);
                o[1] += pw * __uint_as_float(vv[u].x & 0xffff0000u);
                o[2] += pw * __uint_as_float(vv[u].y << 16);
                o[3] += pw * __uint_as_float(vv[u].y & 0xffff0000u);
            }
        }
        const float inv = 1.f / l;
#pragma unroll
        for (int u = 0; u < 4; u++) {
            const int d = 4 * lane + u;
            unsigned short* a = reinterpret_cast<unsigned short*>(
                os + (d >> 5) * 10240 + (qn >> 5) * 2048 + (d & 31) * 64 + ((((qn & 31) >> 3) ^ ((d & 7) >> 1)) << 4) + (qn & 7) * 2);
            *a = (unsigned short)(pack_bf16(o[u] * inv, 0.f) & 0xffffu);
        }
    }
}

__global__ void __launch_bounds__(512, 1) mha_fused_kernel(const __grid_constant__ Params prm) {
    extern __shared__ __align__(1024) unsigned char smem_raw[];
    if ((uint32_t)__cvta_generic_to_shared(smem_raw) != sb) __trap();
    const int cta = blockIdx.x;
    const int g = cta >> 3, j = cta & 7;
    const int br = g >> 3, b = g & 7;
    const int wg = __shfl_sync(0xffffffffu, threadIdx.x >> 7, 0);
    const int warp = __shfl_sync(0xffffffffu, (threadIdx.x >> 5) & 3, 0);
    const int lane = threadIdx.x & 31;

    if (threadIdx.x == 0) {
        for (int i = 0; i < 2; i++) {
            mbar_init(sb + B_KFULL + 8 * i, 1);
            mbar_init(sb + B_KEMPTY + 8 * i, 4);
            mbar_init(sb + B_VFULL + 8 * i, 1);
            mbar_init(sb + B_VEMPTY + 8 * i, 4);
            mbar_init(sb + B_PFULL + 8 * i, 4);
            mbar_init(sb + B_PEMPTY + 8 * i, 4);
        }
        mbar_init(sb + B_QFULL, 1);
        mbar_init(sb + B_QFULL + 8, 1);
        mbar_init(sb + B_KVGO, 4);
        mbar_init(sb + B_KVGO + 8, 4);
        mbar_init(sb + B_QFREE, 4);
        for (int i = 0; i < 4; i++) {
            mbar_init(sb + B_QREADY + 8 * i, 4);
            mbar_init(sb + B_ODONE + 8 * i, 4);
            mbar_init(sb + B_QVIS + 8 * i, 1);
        }
        for (int i = 0; i < 12; i++) {
            mbar_init(sb + B_PRFULL + 8 * i, 1);
            mbar_init(sb + B_PREMPTY + 8 * i, 4);
        }
        for (int i = 0; i < 32; i++) mbar_init(sb + B_ORDY + 8 * i, 1);
        asm volatile("fence.mbarrier_init.release.cluster;" ::: "memory");
        asm volatile("fence.proxy.async.shared::cta;" ::: "memory");
    }
    __syncthreads();
    if (wg == 1) { TR(7, 0); TRG(7, 1); }

    if (wg == 0) {
        asm volatile("setmaxnreg.dec.sync.aligned.u32 24;");
        if (warp == 0) {
            if (lane == 0) {
                const int row0 = (b * NH + j) * SK;
                mbar_wait(sb + B_KVGO, 0);
#pragma unroll 1
                for (int t = 0; t < 65; t++) {
                    if (t < 64) {
                        const uint32_t s = t & 1;
                        const bool newq = (t & 15) == 1 && t > 1;
                        const unsigned char* qsrc = g_scr + (size_t)(g * 32 + ((t >> 4) - 1) * 8 + j) * 40960;
                        if (newq) {
                            mbar_wait(sb + B_QVIS + 8 * (t >> 4), 0);
                            mbar_wait(sb + B_QFREE, ((t >> 4) & 1) ^ 1);
                            mbar_expect(sb + B_QFULL, 20480);
                            bulk_g2s(sb + SM_Q, qsrc, 20480, sb + B_QFULL);
                        }
                        mbar_wait(sb + B_KEMPTY + 8 * s, ((t >> 1) & 1) ^ 1);
                        if (newq) {
                            mbar_expect(sb + B_QFULL + 8, 20480);
                            bulk_g2s(sb + SM_Q + 20480, qsrc + 20480, 20480, sb + B_QFULL + 8);
                        }
                        mbar_expect(sb + B_KFULL + 8 * s, 16384);
                        tma3_hint(sb + SM_K + s * 16384, &prm.k[br], 0, row0 + (t >> 4) * (8 * SK) + (t & 15) * 64, 0,
                                  sb + B_KFULL + 8 * s, POL_EF);
                    }
                    if (t == 1) mbar_wait(sb + B_KVGO + 8, 0);
#pragma unroll 1
                    for (int u = t == 2 ? 2 : t - 1; u >= 0 && u < (t == 1 ? 2 : t); u++) {
                        const uint32_t s = u & 1;
                        mbar_wait(sb + B_VEMPTY + 8 * s, ((u >> 1) & 1) ^ 1);
                        mbar_expect(sb + B_VFULL + 8 * s, 16384);
                        tma3_hint(sb + SM_V + s * 16384, &prm.v[br], 0, row0 + (u >> 4) * (8 * SK) + (u & 15) * 64, 0,
                                  sb + B_VFULL + 8 * s, POL_EF);
                    }
                }
            }
        } else if (warp == 1) {
            if (lane == 0) {
                const unsigned int target = g_epoch[cta] + 1;
#pragma unroll 1
                for (int r = 0; r < 4; r++) {
                    mbar_wait(sb + B_ODONE + 8 * r, 0);
                    asm volatile("st.release.gpu.global.u32 [%0], %1;" ::"l"(g_flag + g * 32 + r * 8 + j), "r"(target) : "memory");
                    TR(3, 10 + r);
                }
            }
        } else if (warp == 2) {
            if (lane == 0) {
#pragma unroll 1
                for (int n = 0; n < 128; n++) {
                    uint32_t s, par;
                    pr_slot(n, s, par);
                    mbar_wait(sb + B_PREMPTY + 8 * s, par ^ 1);
                    const uint32_t dst = sb + s * PR_BYTES, bar = sb + B_PRFULL + 8 * s;
                    mbar_expect(bar, PR_BYTES);
                    tmaw(dst, &prm.wq[br], (n & 31) * 32, 2 * ((n >> 5) * 8 + j), bar);
                    tma2(dst + 8192, &prm.x[br], (n & 31) * 32, b * SQ, bar);
                    if (n == 11) {
                        pf2(&prm.x[br], (6 + j) * 64, b * SQ);
                        for (int m = 12 + ((b + 4) & 7); m < 32; m += 8) pfw(&prm.wq[br], m * 32, 2 * j);
                        if (j < 2) pf2(&prm.x[br], (14 + j) * 64, b * SQ);
                    }
                    const int m = n + PD;
                    if (n >= 12) {
                        if ((m & 7) == b) {
                            if (m < 128) pfw(&prm.wq[br], (m & 31) * 32, 2 * ((m >> 5) * 8 + j));
                            else pfw(&prm.wo[br], (m - 128) * 32, 2 * j);
                        }
                        if (m >= 64 && m < 128 && (m & 15) == 2 * j) pf2(&prm.x[br], (m & 31) * 32, b * SQ);
                    }
                }
                const unsigned char* osrc = g_scr + (size_t)g * (128 * 10240);
#pragma unroll 1
                for (int n = 0; n < 128; n++) {
                    uint32_t s, par;
                    pr_slot(128 + n, s, par);
                    if (n == 100) mbar_wait(sb + B_ODONE + 24, 0);
                    mbar_wait(sb + B_PREMPTY + 8 * s, par ^ 1);
                    const uint32_t dst = sb + s * PR_BYTES, bar = sb + B_PRFULL + 8 * s;
                    mbar_expect(bar, PR_BYTES);
                    tmaw(dst, &prm.wo[br], n * 32, 2 * j, bar);
                    if ((n & 3) == 0) mbar_wait(sb + B_ORDY + 2 * n, 0);
                    bulk_g2s(dst + 8192, osrc + n * 10240, 10240, bar);
                    if (n + PD < 128 && ((n + PD) & 7) == b) pfw(&prm.wo[br], (n + PD) * 32, 2 * j);
                }
            }
        } else {
            const unsigned int target = g_epoch[cta] + 1;
            if (lane == 0) {
#pragma unroll 1
                for (int r = 1; r < 4; r++) {
                    mbar_wait(sb + B_QREADY + 8 * r, 0);
                    asm volatile("fence.acq_rel.gpu;" ::: "memory");
                    asm volatile("fence.proxy.async.global;" ::: "memory");
                    mbar_arrive(sb + B_QVIS + 8 * r);
                    if (r == 2) break;
                }
            }
            __syncwarp();
            int nr = 0;
            bool q3 = false;
            unsigned int it = 0;
            while (nr < 32) {
                if (!q3 && mbar_test(sb + B_QREADY + 24, 0)) {
                    if (lane == 0) {
                        asm volatile("fence.acq_rel.gpu;" ::: "memory");
                        asm volatile("fence.proxy.async.global;" ::: "memory");
                        mbar_arrive(sb + B_QVIS + 24);
                    }
                    q3 = true;
                }
                unsigned int v;
                asm volatile("ld.acquire.gpu.global.u32 %0, [%1];" : "=r"(v) : "l"(g_flag + g * 32 + lane) : "memory");
                const unsigned int miss = ~__ballot_sync(0xffffffffu, v == target);
                const int nn = miss ? __ffs(miss) - 1 : 32;
                if (nn > nr) {
                    asm volatile("fence.proxy.async.global;" ::: "memory");
                    if (lane >= nr && lane < nn) mbar_arrive(sb + B_ORDY + 8 * lane);
                    nr = nn;
                }
                if (!mbar_test(sb + B_ODONE + 24, 0)) __nanosleep(300);
                if (++it > 33554432u) __trap();
                __syncwarp();
            }
            if (lane == 0) g_epoch[cta] = target;
        }
    } else if (wg == 1) {
        asm volatile("setmaxnreg.dec.sync.aligned.u32 104;");
        float s[40], x[40];
#pragma unroll
        for (int i = 0; i < 40; i++) s[i] = x[i] = 0.f;
        const uint32_t t8 = lane & 7, m = lane >> 3;
        const uint32_t pst = sb + SM_P + (8 * (m >> 1) + t8) * 128 + (((2 * warp + (m & 1)) ^ t8) << 4);
        auto qk = [&](uint32_t sl, int hf, int k0, int k1) {
            const uint64_t da = mkdesc<16, 1024, 1>(sb + SM_K + sl * 16384);
            const uint64_t db = mkdesc<4096, 256, 3>(sb + SM_Q + hf * 20480);
            if (k0 == 0) wg_fence();
#pragma unroll
            for (int kk = 0; kk < 8; kk++)
                if (kk >= k0 && kk < k1)
                    wgmma80<0, 1>(s, da + (((kk >> 2) * 8192 + (kk & 3) * 32) >> 4), db + ((kk * 512) >> 4), kk != 0 ? 1 : prm.zero);
            if (k1 == 8) wg_commit();
        };
        auto expo = [&](uint32_t pa, int jj) {
            stsm4t(pa + jj * 2048, pack_bf16(ex2(x[8 * jj]), ex2(x[8 * jj + 1])), pack_bf16(ex2(x[8 * jj + 2]), ex2(x[8 * jj + 3])),
                   pack_bf16(ex2(x[8 * jj + 4]), ex2(x[8 * jj + 5])), pack_bf16(ex2(x[8 * jj + 6]), ex2(x[8 * jj + 7])));
        };
        auto stage = [&]() {
            wg_wait<0>();
            acc_fence(s);
#pragma unroll
            for (int i = 0; i < 40; i++) x[i] = s[i] * QSCALE;
            acc_fence(x);
        };
        mbar_wait(sb + B_QREADY, 0);
        mbar_wait(sb + B_KFULL, 0);
        qk(0, 0, 0, 8);
#pragma unroll 1
        for (int t = 0; t < 64; t++) {
            const uint32_t sl = t & 1, ph = (t >> 1) & 1;
            const uint32_t pa = pst + sl * P_BYTES;
            TR(0, t * 5);
            if ((t & 7) == 0) TRG(6, t);
            mbar_wait(sb + B_PEMPTY + 8 * sl, ph ^ 1);
            if ((t & 15) == 0 && t != 0) mbar_wait(sb + B_QFULL + 8, ((t >> 4) & 1) ^ 1);
            stage();
            TR2(0, t * 5 + 1);
            if ((t & 15) == 15 && lane == 0) mbar_arrive(sb + B_QFREE);
            qk(sl, 1, 0, QS1);
            expo(pa, 0);
            qk(sl, 1, QS1, QS2);
            expo(pa, 1);
            qk(sl, 1, QS2, 8);
            mbar_wait(sb + B_KFULL + 8 * sl, ph);
            expo(pa, 2);
            expo(pa, 3);
            expo(pa, 4);
            TR2(0, t * 5 + 2);
            stage();
            TR2(0, t * 5 + 3);
            if (lane == 0) mbar_arrive(sb + B_KEMPTY + 8 * sl);
            if (t != 63) {
                if ((t & 15) == 15) mbar_wait(sb + B_QFULL, (t >> 4) & 1);
                mbar_wait(sb + B_KFULL + 8 * (sl ^ 1), ((t + 1) >> 1) & 1);
                qk(sl ^ 1, 0, 0, QS1);
                expo(pa + 10240, 0);
                qk(sl ^ 1, 0, QS1, QS2);
                expo(pa + 10240, 1);
                qk(sl ^ 1, 0, QS2, 8);
            } else {
                expo(pa + 10240, 0);
                expo(pa + 10240, 1);
            }
            expo(pa + 10240, 2);
            expo(pa + 10240, 3);
            expo(pa + 10240, 4);
            asm volatile("fence.proxy.async.shared::cta;" ::: "memory");
            __syncwarp();
            if (lane == 0) mbar_arrive(sb + B_PFULL + 8 * sl);
            TR2(0, t * 5 + 4);
        }
        wg_wait<0>();
    } else if (wg == 2) {
        asm volatile("setmaxnreg.inc.sync.aligned.u32 192;");
        float o0[80], o1[80];
        const uint32_t prow = warp * 8 + (lane >> 2);
        const uint32_t pld = sb + SM_P + prow * 128 + (((lane & 3) | ((prow & 1) << 2)) << 4);
#pragma unroll 1
        for (int r = 0; r < 4; r++) {
            float l[5] = {0.f, 0.f, 0.f, 0.f, 0.f};
            bool bad = false;
#pragma unroll 1
            for (int i = 0; i < 16; i++) {
                const uint32_t sl = i & 1, ph = (i >> 1) & 1;
                mbar_wait(sb + B_VFULL + 8 * sl, ph);
                TR2(1, (r * 16 + i) * 3);
                mbar_wait(sb + B_PFULL + 8 * sl, ph);
                TR2(1, (r * 16 + i) * 3 + 1);
                const uint64_t da = mkdesc<16, 1024, 1>(sb + SM_V + sl * 16384);
                const uint64_t db = mkdesc<16, 1024, 1>(sb + SM_P + sl * P_BYTES);
                wg_fence();
#pragma unroll
                for (int k = 0; k < 8; k++) {
                    if (k >= PVW) wg_wait<PVW - 1>();
                    if (k & 1) wgmma160<1, 0>(o1, da + ((8192 + (k >> 1) * 2048) >> 4), db + (((k >> 1) * 32) >> 4), ((k >> 1) | i) != 0);
                    else wgmma160<1, 0>(o0, da + (((k >> 1) * 2048) >> 4), db + (((k >> 1) * 32) >> 4), ((k >> 1) | i) != 0);
                    wg_commit();
                    if (k >= 3) {
                        uint32_t w0, w1, w2, w3, w4, w5, w6, w7;
                        asm volatile("ld.shared.v4.u32 {%0, %1, %2, %3}, [%4];" : "=r"(w0), "=r"(w1), "=r"(w2), "=r"(w3)
                                     : "r"(pld + sl * P_BYTES + (k - 3) * 4096) : "memory");
                        asm volatile("ld.shared.v4.u32 {%0, %1, %2, %3}, [%4];" : "=r"(w4), "=r"(w5), "=r"(w6), "=r"(w7)
                                     : "r"(((pld + sl * P_BYTES) ^ 64) + (k - 3) * 4096) : "memory");
                        const uint32_t w = hadd2(hadd2(hadd2(w0, w1), hadd2(w2, w3)), hadd2(hadd2(w4, w5), hadd2(w6, w7)));
                        l[k - 3] += __uint_as_float(w << 16) + __uint_as_float(w & 0xffff0000u);
                    }
                }
                if (i == 15) {
#pragma unroll
                    for (int k = 0; k < 5; k++) l[k] += __shfl_xor_sync(0xffffffffu, l[k], 1);
#pragma unroll
                    for (int k = 0; k < 5; k++) l[k] += __shfl_xor_sync(0xffffffffu, l[k], 2);
                    const uint32_t la = sb + SM_LINV + (((prow >> 1) & 3) * 8 + (prow >> 3) * 2 + (prow & 1)) * 4;
#pragma unroll
                    for (int k = 0; k < 5; k++) {
                        bad |= !(l[k] >= 0.00390625f && l[k] <= 4294967296.f);
                        float v;
                        asm("rcp.approx.ftz.f32 %0, %1;" : "=f"(v) : "f"(l[k]));
                        if ((lane & 3) == 0) asm volatile("st.shared.f32 [%0], %1;" ::"r"(la + 128 * k), "f"(v) : "memory");
                    }
                }
                wg_wait<0>();
                __syncwarp();
                TR2(1, (r * 16 + i) * 3 + 2);
                if (lane == 0) {
                    mbar_arrive(sb + B_PEMPTY + 8 * sl);
                    mbar_arrive(sb + B_VEMPTY + 8 * sl);
                }
            }
            acc_fence(o0);
            acc_fence(o1);
            TR(4, r * 4);
            uint32_t redo;
            asm volatile("{\n.reg .pred p, q;\nsetp.ne.u32 p, %1, 0;\nbar.red.or.pred q, 1, 128, p;\nselp.u32 %0, 1, 0, q;\n}"
                         : "=r"(redo) : "r"((uint32_t)bad) : "memory");
            TR(4, r * 4 + 1);
            if (r < 3) mbar_wait(sb + B_QFULL + 8, r & 1);
            unsigned char* os = g_scr + (size_t)(g * 32 + 8 * r + j) * 40960;
            if (redo) {
                const int h = 8 * r + j;
                slow_head(prm.xp[br] + (size_t)b * SQ * 1024, prm.wqp[br] + h * 128, prm.kp[br] + (size_t)(b * NH + h) * SK * 128,
                          prm.vp[br] + (size_t)(b * NH + h) * SK * 128, os, warp, lane);
#pragma unroll
                for (int z = 0; z < 80; z++) { o0[z] = 0.f; o1[z] = 0.f; }
            } else {
                const uint32_t g8 = lane >> 2;
                unsigned char* op = os + (warp >> 1) * 10240 + (16 * (warp & 1) + g8) * 64 + (((lane & 3) ^ (g8 >> 1)) << 4);
                const uint32_t li = (lane & 3) * 32;
                float iv[40];
                lds128i<sb + SM_LINV>(li, iv);
                lds128i<sb + SM_LINV + 16>(li, iv + 4);
                static_for<5>([&](auto I) {
                    constexpr int i = I.value, a = 16 * i;
                    constexpr uint32_t O0 = i * 2048, O1 = 20480 + i * 2048;
                    const float* v = iv + 8 * i;
                    stg128(op + O0, pack_bf16(o0[a] * v[0], o0[a + 1] * v[1]), pack_bf16(o0[a + 4] * v[2], o0[a + 5] * v[3]),
                                pack_bf16(o0[a + 8] * v[4], o0[a + 9] * v[5]), pack_bf16(o0[a + 12] * v[6], o0[a + 13] * v[7]));
                    if constexpr (i < 4) {
                        lds128i<sb + SM_LINV + 128 * (i + 1)>(li, iv + 8 * (i + 1));
                        lds128i<sb + SM_LINV + 128 * (i + 1) + 16>(li, iv + 8 * (i + 1) + 4);
                    }
                    stg128(op + O0 + 512, pack_bf16(o0[a + 2] * v[0], o0[a + 3] * v[1]), pack_bf16(o0[a + 6] * v[2], o0[a + 7] * v[3]),
                                      pack_bf16(o0[a + 10] * v[4], o0[a + 11] * v[5]), pack_bf16(o0[a + 14] * v[6], o0[a + 15] * v[7]));
                    stg128(op + O1, pack_bf16(o1[a] * v[0], o1[a + 1] * v[1]), pack_bf16(o1[a + 4] * v[2], o1[a + 5] * v[3]),
                                pack_bf16(o1[a + 8] * v[4], o1[a + 9] * v[5]), pack_bf16(o1[a + 12] * v[6], o1[a + 13] * v[7]));
                    stg128(op + O1 + 512, pack_bf16(o1[a + 2] * v[0], o1[a + 3] * v[1]), pack_bf16(o1[a + 6] * v[2], o1[a + 7] * v[3]),
                                      pack_bf16(o1[a + 10] * v[4], o1[a + 11] * v[5]), pack_bf16(o1[a + 14] * v[6], o1[a + 15] * v[7]));
                });
            }
            TR(4, r * 4 + 2);
            __syncwarp();
            if (lane == 0) mbar_arrive(sb + B_ODONE + 8 * r);
            TR(3, r);
        }
    } else {
        asm volatile("setmaxnreg.inc.sync.aligned.u32 192;");
        float a0[80], a1[80];
        uint32_t sprev = 0;
#pragma unroll 1
        for (int r = 0; r < 4; r++) {
#pragma unroll 1
            for (int n = 0; n < 32; n++) {
                uint32_t s, ph;
                pr_slot(r * 32 + n, s, ph);
                TR2(2, (r * 32 + n) * 2);
                mbar_wait(sb + B_PRFULL + 8 * s, ph);
                TR2(2, (r * 32 + n) * 2 + 1);
                if ((n & 7) == 0 || n == 31) TR(2, (r * 32 + n) * 2 + 1);
                const uint64_t da = mkdesc<16, 1024, 1>(sb + s * PR_BYTES);
                const uint64_t db = mkdesc<16, 512, 2>(sb + s * PR_BYTES + 8192);
                const uint32_t rel = n != 0 ? sb + B_PREMPTY + 8 * sprev : 0;
                if (r == 0 && lane == 0) {
                    if (n == K_START) mbar_arrive(sb + B_KVGO);
                    if (n == V_START) mbar_arrive(sb + B_KVGO + 8);
                }
                if (PW != PWD && r == 0) proj_stage<PWD, 0, 32>(a0, a1, da, db, n != 0, rel, lane == 0);
                else proj_stage<PW, 0, 32>(a0, a1, da, db, n != 0, rel, lane == 0);
                sprev = s;
            }
            wg_wait<0>();
            acc_fence(a0);
            acc_fence(a1);
            TR(4, 16 + r);
            if (lane == 0) mbar_arrive(sb + B_PREMPTY + 8 * sprev);
            const uint32_t g8 = lane >> 2;
            const uint32_t qo = ((lane >> 1) & 1) * 4096 + (16 * warp + g8) * 32 + (((lane & 1) ^ (g8 >> 2)) << 4);
            if (r == 0) {
                static_for<20>([&](auto I) {
                    constexpr int i = I.value, a = 16 * (i >> 2) + 2 * (i & 1);
                    const float* v = (i & 2) ? a1 : a0;
                    sts128i<sb + SM_Q + (i >> 2) * 8192 + ((i >> 1) & 1) * 2048 + (i & 1) * 256>(
                        qo, pack_bf16(v[a], v[a + 1]), pack_bf16(v[a + 4], v[a + 5]), pack_bf16(v[a + 8], v[a + 9]),
                        pack_bf16(v[a + 12], v[a + 13]));
                });
                asm volatile("fence.proxy.async.shared::cta;" ::: "memory");
            } else {
                unsigned char* qp = g_scr + (size_t)(g * 32 + (r - 1) * 8 + j) * 40960 + qo;
#pragma unroll
                for (int i = 0; i < 20; i++) {
                    const int a = 16 * (i >> 2) + 2 * (i & 1);
                    const float* v = (i & 2) ? a1 : a0;
                    stg128(qp + (i >> 2) * 8192 + ((i >> 1) & 1) * 2048 + (i & 1) * 256, pack_bf16(v[a], v[a + 1]),
                           pack_bf16(v[a + 4], v[a + 5]), pack_bf16(v[a + 8], v[a + 9]), pack_bf16(v[a + 12], v[a + 13]));
                }
            }
            __syncwarp();
            if (lane == 0) mbar_arrive(sb + B_QREADY + 8 * r);
            TR(3, 4 + r);
        }
#pragma unroll 1
        for (int n = 0; n < 128; n++) {
            uint32_t s, ph;
            pr_slot(128 + n, s, ph);
            TR2(2, (128 + n) * 2);
            mbar_wait(sb + B_PRFULL + 8 * s, ph);
            TR2(2, (128 + n) * 2 + 1);
            if ((n & 7) == 0 || (n & 31) == 31) TR(2, (128 + n) * 2 + 1);
            const uint64_t da = mkdesc<16, 1024, 1>(sb + s * PR_BYTES);
            const uint64_t db = mkdesc<2048, 512, 2>(sb + s * PR_BYTES + 8192);
            const uint32_t rel = n != 0 ? sb + B_PREMPTY + 8 * sprev : 0;
            if (PW != PWD && n >= 96) proj_stage<PWD, 1, 1024>(a0, a1, da, db, n != 0, rel, lane == 0);
            else proj_stage<PW, 1, 1024>(a0, a1, da, db, n != 0, rel, lane == 0);
            sprev = s;
        }
        wg_wait<0>();
        acc_fence(a0);
        acc_fence(a1);
        TR(4, 20);
        asm volatile("bar.sync 2, 128;" ::: "memory");
        const uint32_t t8 = lane & 7, m = lane >> 3;
        const uint32_t pst = sb + SM_P + (8 * (m >> 1) + t8) * 128 + (((2 * warp + (m & 1)) ^ t8) << 4);
#pragma unroll
        for (int jj = 0; jj < 10; jj++) {
            stsm4t(pst + jj * 2048, pack_bf16(a0[8 * jj], a0[8 * jj + 1]), pack_bf16(a0[8 * jj + 2], a0[8 * jj + 3]),
                   pack_bf16(a0[8 * jj + 4], a0[8 * jj + 5]), pack_bf16(a0[8 * jj + 6], a0[8 * jj + 7]));
            stsm4t(pst + P_BYTES + jj * 2048, pack_bf16(a1[8 * jj], a1[8 * jj + 1]), pack_bf16(a1[8 * jj + 2], a1[8 * jj + 3]),
                   pack_bf16(a1[8 * jj + 4], a1[8 * jj + 5]), pack_bf16(a1[8 * jj + 6], a1[8 * jj + 7]));
        }
        asm volatile("fence.proxy.async.shared::cta;" ::: "memory");
        asm volatile("bar.sync 2, 128;" ::: "memory");
        TR(4, 21);
        if (warp == 0 && lane == 0) {
            tma2_store(&prm.out, sb + SM_P, br * 1024 + j * 128, b * SQ);
            tma2_store(&prm.out, sb + SM_P + P_BYTES, br * 1024 + j * 128 + 64, b * SQ);
            asm volatile("cp.async.bulk.commit_group;" ::: "memory");
            asm volatile("cp.async.bulk.wait_group 0;" ::: "memory");
            TR(3, 8);
            TRG(7, 2);
        }
    }
}

typedef CUresult (*EncodeFn)(CUtensorMap*, CUtensorMapDataType, cuuint32_t, void*, const cuuint64_t*, const cuuint64_t*,
                             const cuuint32_t*, const cuuint32_t*, CUtensorMapInterleave, CUtensorMapSwizzle,
                             CUtensorMapL2promotion, CUtensorMapFloatOOBfill);

#define PROMO_W CU_TENSOR_MAP_L2_PROMOTION_L2_128B
#define PROMO_KV CU_TENSOR_MAP_L2_PROMOTION_L2_128B
void encode(EncodeFn fn, CUtensorMap* m, void* p, int rank, const cuuint64_t* dims, const cuuint64_t* strides,
            const cuuint32_t* box, CUtensorMapSwizzle swz, CUtensorMapL2promotion promo = PROMO_W) {
    cuuint32_t es[3] = {1, 1, 1};
    fn(m, CU_TENSOR_MAP_DATA_TYPE_BFLOAT16, rank, p, dims, strides, box, es, CU_TENSOR_MAP_INTERLEAVE_NONE, swz,
       promo, CU_TENSOR_MAP_FLOAT_OOB_FILL_NONE);
}

}

extern "C" void kernel_launch(void* const* d_in, const int* in_sizes, int n_in, void* d_out, int out_size) {
    static EncodeFn fn = nullptr;
    if (!fn) {
        void* f = nullptr;
        cudaDriverEntryPointQueryResult st;
        cudaGetDriverEntryPoint("cuTensorMapEncodeTiled", &f, cudaEnableDefault, &st);
        fn = (EncodeFn)f;
        cudaFuncSetAttribute(mha_fused_kernel, cudaFuncAttributeMaxDynamicSharedMemorySize, SM_TOTAL);
    }
    Params prm;
    prm.zero = 0;
    for (int br = 0; br < 2; br++) {
        void* x = d_in[5 * br + 0];
        void* k = d_in[5 * br + 1];
        void* v = d_in[5 * br + 2];
        void* wq = d_in[5 * br + 3];
        void* wo = d_in[5 * br + 4];
        {
            cuuint64_t dims[3] = {64, 8ull * NH * SK, 2}, str[2] = {256, 128};
            cuuint32_t box[3] = {64, 64, 2};
            encode(fn, &prm.k[br], k, 3, dims, str, box, CU_TENSOR_MAP_SWIZZLE_128B, PROMO_KV);
            encode(fn, &prm.v[br], v, 3, dims, str, box, CU_TENSOR_MAP_SWIZZLE_128B, PROMO_KV);
        }
        {
            cuuint64_t dims[3] = {64, 1024, 64}, str[2] = {8192, 128};
            cuuint32_t box[3] = {64, 32, 2};
            encode(fn, &prm.wq[br], wq, 3, dims, str, box, CU_TENSOR_MAP_SWIZZLE_128B);
        }
        {
            cuuint64_t dims[3] = {64, 4096, 16}, str[2] = {2048, 128};
            cuuint32_t box[3] = {64, 32, 2};
            encode(fn, &prm.wo[br], wo, 3, dims, str, box, CU_TENSOR_MAP_SWIZZLE_128B);
        }
        {
            cuuint64_t dims[2] = {1024, 1280}, str[1] = {2048};
            cuuint32_t box[2] = {32, 160};
            encode(fn, &prm.x[br], x, 2, dims, str, box, CU_TENSOR_MAP_SWIZZLE_64B);
        }
        prm.kp[br] = (const __nv_bfloat16*)k;
        prm.vp[br] = (const __nv_bfloat16*)v;
        prm.xp[br] = (const __nv_bfloat16*)x;
        prm.wqp[br] = (const __nv_bfloat16*)wq;
    }
    {
        cuuint64_t dims[2] = {2048, 1280}, str[1] = {4096};
        cuuint32_t box[2] = {64, 160};
        encode(fn, &prm.out, d_out, 2, dims, str, box, CU_TENSOR_MAP_SWIZZLE_128B);
    }
    mha_fused_kernel<<<NCTA, 512, SM_TOTAL, cudaStreamPerThread>>>(prm);
}
```

```cpp
#include <cuda_runtime.h>
#include <cuda_bf16.h>
#include <cuda.h>
#include <stdint.h>

namespace {

constexpr int SQ = 160, SK = 1024, NH = 32;
constexpr int NCTA = 128;

constexpr uint32_t sb = 1024;
constexpr uint32_t PR_BYTES = 18432;
constexpr uint32_t SM_Q = 4 * PR_BYTES;
constexpr uint32_t SM_P = SM_Q + 40960;
constexpr uint32_t P_BYTES = 20480;
constexpr uint32_t SM_K = SM_P + 2 * P_BYTES;
constexpr uint32_t SM_V = SM_K + 2 * 16384;
constexpr uint32_t SM_LINV = SM_V + 2 * 16384;
constexpr uint32_t SM_BAR = SM_LINV + 160 * 4;
constexpr uint32_t SM_ORD = SM_BAR + 768;
constexpr uint32_t SM_TOTAL = SM_ORD + 32;
static_assert(SM_V + 2 * 16384 == 12 * PR_BYTES, "Q/P/K/V double as 8 extra projection slots before and after attention");
constexpr uint32_t B_KFULL = SM_BAR + 0;
constexpr uint32_t B_KEMPTY = SM_BAR + 16;
constexpr uint32_t B_VFULL = SM_BAR + 32;
constexpr uint32_t B_VEMPTY = SM_BAR + 48;
constexpr uint32_t B_PFULL = SM_BAR + 64;
constexpr uint32_t B_PEMPTY = SM_BAR + 80;
constexpr uint32_t B_QFULL = SM_BAR + 96;
constexpr uint32_t B_QREADY = SM_BAR + 112;
constexpr uint32_t B_ODONE = SM_BAR + 144;
constexpr uint32_t B_QVIS = SM_BAR + 176;
constexpr uint32_t B_PRFULL = SM_BAR + 208;
constexpr uint32_t B_PREMPTY = SM_BAR + 304;
constexpr uint32_t B_ORDY = SM_BAR + 400;
constexpr uint32_t B_KVGO = SM_BAR + 656;
constexpr uint32_t B_QFREE = SM_BAR + 672;
constexpr uint32_t B_ADONE = SM_BAR + 680;
#define K_START 7
#define V_START 7
#define QGA 0
#define QGB 1
#define PDQ_ 5
constexpr int PDQ = PDQ_;

#define TQ 63
__device__ __forceinline__ void pr_quad(int q, uint32_t& base, uint32_t& par) {
    if (q > TQ) {
        const int m = q - TQ, w = m >= 6 ? 2 : (m >= 3 ? 1 : 0), k = m - 3 * w;
        base = 4 * k;
        par = (w + (k == 0 ? TQ + 1 : (k == 1 ? 0 : 1))) & 1;
    } else if (q >= 8) {
        base = 0;
        par = (q + 1) & 1;
    } else {
        base = q == 0 ? 8 : 4 * (q & 1);
        par = q == 0 ? 0 : ((q - 1) >> 1) & 1;
    }
}

template <int V> struct IC { static constexpr int value = V; };
template <int N, int I = 0, class F> __device__ __forceinline__ void static_for(F&& f) {
    if constexpr (I < N) {
        f(IC<I>{});
        static_for<N, I + 1>(f);
    }
}

struct Params {
    CUtensorMap k[2], v[2], x[2], wq[2], wo[2], out;
    const __nv_bfloat16* kp[2];
    const __nv_bfloat16* vp[2];
    const __nv_bfloat16* xp[2];
    const __nv_bfloat16* wqp[2];
    int zero;
    int never;
};

__device__ __align__(1024) unsigned char g_scr[16 * 32 * 40960];
__device__ __align__(128) unsigned int g_flag[16 * 32];
__device__ unsigned int g_epoch[NCTA];

#define TR(role, idx)
#define TRG(role, idx)
#define TR2(role, idx)

__device__ __forceinline__ void mbar_init(uint32_t b, int c) {
    asm volatile("mbarrier.init.shared::cta.b64 [%0], %1;" ::"r"(b), "r"(c));
}
__device__ __forceinline__ void mbar_expect(uint32_t b, int bytes) {
    asm volatile("mbarrier.arrive.expect_tx.shared::cta.b64 _, [%0], %1;" ::"r"(b), "r"(bytes) : "memory");
}
__device__ __forceinline__ void mbar_arrive(uint32_t b) {
    asm volatile("mbarrier.arrive.shared::cta.b64 _, [%0];" ::"r"(b) : "memory");
}
__device__ __forceinline__ void mbar_arrive_warp(uint32_t b) {
    asm volatile("{\n.reg .pred p;\nelect.sync _|p, 0xffffffff;\n@p mbarrier.arrive.shared::cta.b64 _, [%0];\n}" ::"r"(b) : "memory");
}
__device__ __forceinline__ bool elect_one() {
    uint32_t r;
    asm volatile("{\n.reg .pred p;\nelect.sync _|p, 0xffffffff;\nselp.u32 %0, 1, 0, p;\n}" : "=r"(r));
    return r != 0;
}
__device__ __forceinline__ uint32_t warp_now() {
    uint32_t r;
    asm volatile("mov.u32 %0, %tid.x;" : "=r"(r));
    return (r >> 5) & 3;
}
__device__ __forceinline__ uint32_t lane_now() {
    uint32_t r;
    asm volatile("mov.u32 %0, %laneid;" : "=r"(r));
    return r;
}
__device__ __forceinline__ void mbar_wait(uint32_t b, uint32_t ph) {
    asm volatile(
        "{\n.reg .pred p;\n.reg .u32 n;\n"
        "mbarrier.try_wait.parity.shared::cta.b64 p, [%0], %1;\n"
        "@p bra D;\n"
        "mov.u32 n, 0;\n"
        "W:\nmbarrier.try_wait.parity.shared::cta.b64 p, [%0], %1;\n"
        "@p bra D;\n"
        "add.u32 n, n, 1;\nsetp.lt.u32 p, n, 33554432;\n@p bra W;\ntrap;\n"
        "D:\n}" ::"r"(b), "r"(ph) : "memory");
}
__device__ __forceinline__ bool mbar_test(uint32_t b, uint32_t ph) {
    uint32_t r;
    asm volatile("{\n.reg .pred p;\nmbarrier.test_wait.parity.shared::cta.b64 p, [%1], %2;\nselp.u32 %0, 1, 0, p;\n}"
                 : "=r"(r) : "r"(b), "r"(ph) : "memory");
    return r != 0;
}
__device__ __forceinline__ void pf3(const CUtensorMap* m, int c0, int c1, int c2) {
    asm volatile("cp.async.bulk.prefetch.tensor.3d.L2.global [%0, {%1, %2, %3}];" ::"l"(m), "r"(c0), "r"(c1), "r"(c2) : "memory");
}
constexpr uint64_t POL_EF = 0x12F0000000000000ull;
__device__ __forceinline__ void pf2(const CUtensorMap* m, int c0, int c1) {
    asm volatile("cp.async.bulk.prefetch.tensor.2d.L2.global [%0, {%1, %2}];" ::"l"(m), "r"(c0), "r"(c1) : "memory");
}
__device__ __forceinline__ void pfb(const void* p, int bytes) {
    asm volatile("cp.async.bulk.prefetch.L2.global [%0], %1;" ::"l"(p), "r"(bytes) : "memory");
}
__device__ __forceinline__ void sts128(uint32_t p, uint32_t a, uint32_t b, uint32_t c, uint32_t d) {
    asm volatile("st.shared.v4.u32 [%0], {%1, %2, %3, %4};" ::"r"(p), "r"(a), "r"(b), "r"(c), "r"(d) : "memory");
}
__device__ __forceinline__ void tma3(uint32_t dst, const CUtensorMap* m, int c0, int c1, int c2, uint32_t bar) {
    asm volatile("cp.async.bulk.tensor.3d.shared::cluster.global.mbarrier::complete_tx::bytes [%0], [%1, {%3, %4, %5}], [%2];"
                 ::"r"(dst), "l"(m), "r"(bar), "r"(c0), "r"(c1), "r"(c2) : "memory");
}
__device__ __forceinline__ void tma3_hint(uint32_t dst, const CUtensorMap* m, int c0, int c1, int c2, uint32_t bar, uint64_t pol) {
    asm volatile("cp.async.bulk.tensor.3d.shared::cluster.global.mbarrier::complete_tx::bytes.L2::cache_hint [%0], [%1, {%3, %4, %5}], [%2], %6;"
                 ::"r"(dst), "l"(m), "r"(bar), "r"(c0), "r"(c1), "r"(c2), "l"(pol) : "memory");
}
__device__ __forceinline__ void tma2(uint32_t dst, const CUtensorMap* m, int c0, int c1, uint32_t bar) {
    asm volatile("cp.async.bulk.tensor.2d.shared::cluster.global.mbarrier::complete_tx::bytes [%0], [%1, {%3, %4}], [%2];"
                 ::"r"(dst), "l"(m), "r"(bar), "r"(c0), "r"(c1) : "memory");
}
__device__ __forceinline__ void bulk_g2s(uint32_t dst, const void* src, int bytes, uint32_t bar) {
    asm volatile("cp.async.bulk.shared::cluster.global.mbarrier::complete_tx::bytes [%0], [%1], %2, [%3];"
                 ::"r"(dst), "l"(src), "r"(bytes), "r"(bar) : "memory");
}
__device__ __forceinline__ void bulk_s2g(void* dst, uint32_t src, int bytes) {
    asm volatile("cp.async.bulk.global.shared::cta.bulk_group [%0], [%1], %2;" ::"l"(dst), "r"(src), "r"(bytes) : "memory");
}
__device__ __forceinline__ void mbar_arrive4(uint32_t b) {
    asm volatile("mbarrier.arrive.shared::cta.b64 _, [%0], 4;" ::"r"(b) : "memory");
}
__device__ __forceinline__ void tma2_store(const CUtensorMap* m, uint32_t src, int c0, int c1) {
    asm volatile("cp.async.bulk.tensor.2d.global.shared::cta.bulk_group [%0, {%2, %3}], [%1];"
                 ::"l"(m), "r"(src), "r"(c0), "r"(c1) : "memory");
}
__device__ __forceinline__ void wg_fence() { asm volatile("wgmma.fence.sync.aligned;" ::: "memory"); }
__device__ __forceinline__ void wg_commit() { asm volatile("wgmma.commit_group.sync.aligned;" ::: "memory"); }
template <int N> __device__ __forceinline__ void wg_wait() { asm volatile("wgmma.wait_group.sync.aligned %0;" ::"n"(N) : "memory"); }
template <int N> __device__ __forceinline__ void acc_fence(float (&d)[N]) {
#pragma unroll
    for (int i = 0; i < N; i++) asm volatile("" : "+f"(d[i])::"memory");
}
template <uint32_t OFF> __device__ __forceinline__ void sts128i(uint32_t p, uint32_t a, uint32_t b, uint32_t c, uint32_t d) {
    asm volatile("st.shared.v4.u32 [%0+%5], {%1, %2, %3, %4};" ::"r"(p), "r"(a), "r"(b), "r"(c), "r"(d), "n"(OFF) : "memory");
}
template <uint32_t OFF> __device__ __forceinline__ void lds128i(uint32_t p, float* v) {
    asm volatile("ld.shared.v4.f32 {%0, %1, %2, %3}, [%4+%5];" : "=f"(v[0]), "=f"(v[1]), "=f"(v[2]), "=f"(v[3]) : "r"(p), "n"(OFF) : "memory");
}
template <uint32_t OFF> __device__ __forceinline__ void lds128u(uint32_t p, uint32_t* v) {
    asm volatile("ld.shared.v4.u32 {%0, %1, %2, %3}, [%4+%5];" : "=r"(v[0]), "=r"(v[1]), "=r"(v[2]), "=r"(v[3]) : "r"(p), "n"(OFF) : "memory");
}
#define SCHED_FENCE(cnt, k) do { if ((cnt) == prm.never + (int)(k)) { wg_wait<0>(); __trap(); } } while (0)
template <uint32_t LBO, uint32_t SBO, uint32_t SWZ>
__device__ __forceinline__ uint64_t mkdesc(uint32_t addr) {
    uint32_t lo = ((addr & 0x3FFFF) >> 4) | ((LBO >> 4) << 16);
    uint32_t hi = (SBO >> 4) | (SWZ << 30);
    return ((uint64_t)hi << 32) | lo;
}

template <int TA, int TB>
__device__ __forceinline__ void wgmma160(float (&d)[80], uint64_t da, uint64_t db, int scale_d) {
    asm volatile(
        "{\n.reg .pred p;\nsetp.ne.b32 p, %82, 0;\n"
        "wgmma.mma_async.sync.aligned.m64n160k16.f32.bf16.bf16 "
        "{%0, %1, %2, %3, %4, %5, %6, %7, %8, %9, %10, %11, %12, %13, %14, %15, %16, %17, %18, %19, "
        "%20, %21, %22, %23, %24, %25, %26, %27, %28, %29, %30, %31, %32, %33, %34, %35, %36, %37, %38, %39, "
        "%40, %41, %42, %43, %44, %45, %46, %47, %48, %49, %50, %51, %52, %53, %54, %55, %56, %57, %58, %59, "
        "%60, %61, %62, %63, %64, %65, %66, %67, %68, %69, %70, %71, %72, %73, %74, %75, %76, %77, %78, %79}, "
        "%80, %81, p, 1, 1, %83, %84;\n}\n"
        : "+f"(d[0]), "+f"(d[1]), "+f"(d[2]), "+f"(d[3]), "+f"(d[4]), "+f"(d[5]), "+f"(d[6]), "+f"(d[7]),
          "+f"(d[8]), "+f"(d[9]), "+f"(d[10]), "+f"(d[11]), "+f"(d[12]), "+f"(d[13]), "+f"(d[14]), "+f"(d[15]),
          "+f"(d[16]), "+f"(d[17]), "+f"(d[18]), "+f"(d[19]), "+f"(d[20]), "+f"(d[21]), "+f"(d[22]), "+f"(d[23]),
          "+f"(d[24]), "+f"(d[25]), "+f"(d[26]), "+f"(d[27]), "+f"(d[28]), "+f"(d[29]), "+f"(d[30]), "+f"(d[31]),
          "+f"(d[32]), "+f"(d[33]), "+f"(d[34]), "+f"(d[35]), "+f"(d[36]), "+f"(d[37]), "+f"(d[38]), "+f"(d[39]),
          "+f"(d[40]), "+f"(d[41]), "+f"(d[42]), "+f"(d[43]), "+f"(d[44]), "+f"(d[45]), "+f"(d[46]), "+f"(d[47]),
          "+f"(d[48]), "+f"(d[49]), "+f"(d[50]), "+f"(d[51]), "+f"(d[52]), "+f"(d[53]), "+f"(d[54]), "+f"(d[55]),
          "+f"(d[56]), "+f"(d[57]), "+f"(d[58]), "+f"(d[59]), "+f"(d[60]), "+f"(d[61]), "+f"(d[62]), "+f"(d[63]),
          "+f"(d[64]), "+f"(d[65]), "+f"(d[66]), "+f"(d[67]), "+f"(d[68]), "+f"(d[69]), "+f"(d[70]), "+f"(d[71]),
          "+f"(d[72]), "+f"(d[73]), "+f"(d[74]), "+f"(d[75]), "+f"(d[76]), "+f"(d[77]), "+f"(d[78]), "+f"(d[79])
        : "l"(da), "l"(db), "r"(scale_d), "n"(TA), "n"(TB));
}
template <int TA, int TB>
__device__ __forceinline__ void wgmma80(float (&d)[40], uint64_t da, uint64_t db, int scale_d) {
    asm volatile(
        "{\n.reg .pred p;\nsetp.ne.b32 p, %42, 0;\n"
        "wgmma.mma_async.sync.aligned.m64n80k16.f32.bf16.bf16 "
        "{%0, %1, %2, %3, %4, %5, %6, %7, %8, %9, %10, %11, %12, %13, %14, %15, %16, %17, %18, %19, "
        "%20, %21, %22, %23, %24, %25, %26, %27, %28, %29, %30, %31, %32, %33, %34, %35, %36, %37, %38, %39}, "
        "%40, %41, p, 1, 1, %43, %44;\n}\n"
        : "+f"(d[0]), "+f"(d[1]), "+f"(d[2]), "+f"(d[3]), "+f"(d[4]), "+f"(d[5]), "+f"(d[6]), "+f"(d[7]),
          "+f"(d[8]), "+f"(d[9]), "+f"(d[10]), "+f"(d[11]), "+f"(d[12]), "+f"(d[13]), "+f"(d[14]), "+f"(d[15]),
          "+f"(d[16]), "+f"(d[17]), "+f"(d[18]), "+f"(d[19]), "+f"(d[20]), "+f"(d[21]), "+f"(d[22]), "+f"(d[23]),
          "+f"(d[24]), "+f"(d[25]), "+f"(d[26]), "+f"(d[27]), "+f"(d[28]), "+f"(d[29]), "+f"(d[30]), "+f"(d[31]),
          "+f"(d[32]), "+f"(d[33]), "+f"(d[34]), "+f"(d[35]), "+f"(d[36]), "+f"(d[37]), "+f"(d[38]), "+f"(d[39])
        : "l"(da), "l"(db), "r"(scale_d), "n"(TA), "n"(TB));
}
__device__ __forceinline__ uint32_t pack_bf16(float lo, float hi) {
    uint32_t r;
    asm("cvt.rn.bf16x2.f32 %0, %1, %2;" : "=r"(r) : "f"(hi), "f"(lo));
    return r;
}
__device__ __forceinline__ uint32_t hadd2(uint32_t a, uint32_t b) {
    uint32_t r;
    asm("add.rn.bf16x2 %0, %1, %2;" : "=r"(r) : "r"(a), "r"(b));
    return r;
}
__device__ __forceinline__ void lsum(float& l, const uint32_t* w) {
    const uint32_t t = hadd2(hadd2(hadd2(w[0], w[1]), hadd2(w[2], w[3])), hadd2(hadd2(w[4], w[5]), hadd2(w[6], w[7])));
    l += __uint_as_float(t << 16) + __uint_as_float(t & 0xffff0000u);
}
#define PVW 3
__device__ __forceinline__ float ex2(float x) {
    float r;
    asm("ex2.approx.ftz.f32 %0, %1;" : "=f"(r) : "f"(x));
    return r;
}
__device__ __forceinline__ void stsm4t(uint32_t addr, uint32_t a, uint32_t b, uint32_t c, uint32_t d) {
    asm volatile("stmatrix.sync.aligned.m8n8.x4.trans.shared.b16 [%0], {%1, %2, %3, %4};"
                 ::"r"(addr), "r"(a), "r"(b), "r"(c), "r"(d) : "memory");
}
__device__ __forceinline__ void stg128(void* p, uint32_t a, uint32_t b, uint32_t c, uint32_t d) {
    asm volatile("st.global.v4.u32 [%0], {%1, %2, %3, %4};" ::"l"(p), "r"(a), "r"(b), "r"(c), "r"(d) : "memory");
}

template <int TB> struct PB;
template <> struct PB<0> { static constexpr uint32_t LBO = 16, STEP = 32; };
template <> struct PB<1> { static constexpr uint32_t LBO = 2048, STEP = 1024; };

template <int W, int TB, int cont = 1>
__device__ __forceinline__ void quad_shared(float (&a0)[80], float (&a1)[80], uint32_t par, bool leader) {
    static_for<4>([&](auto I) {
        constexpr uint32_t i = I.value;
        constexpr uint32_t rel = sb + B_PREMPTY + 8 * ((i + 3) & 3);
        const uint64_t da = mkdesc<16, 1024, 1>(sb + i * PR_BYTES);
        const uint64_t db = mkdesc<PB<TB>::LBO, 512, 2>(sb + i * PR_BYTES + 8192);
        constexpr int acc = i == 0 ? cont : 1;
        const bool dorel = leader && (i != 0 || cont);
        constexpr int W0 = W < 10 ? W : W / 1000, W1 = W < 10 ? W : W / 100 % 10, W2 = W < 10 ? W : W / 10 % 10, W3 = W % 10;
        constexpr int RP = W0 <= 1 ? 0 : (W1 <= 2 ? 1 : (W2 <= 3 ? 2 : 3));
        mbar_wait(sb + B_PRFULL + 8 * i, par);
        wg_wait<W0 - 1>();
        if (RP == 0 && dorel) mbar_arrive(rel);
        wg_fence();
        wgmma160<1, TB>(a0, da, db, acc);
        wg_commit();
        wg_wait<W1 - 1>();
        if (RP == 1 && dorel) mbar_arrive(rel);
        wgmma160<1, TB>(a1, da + (4096 >> 4), db, acc);
        wg_commit();
        wg_wait<W2 - 1>();
        if (RP == 2 && dorel) mbar_arrive(rel);
        wgmma160<1, TB>(a0, da + (2048 >> 4), db + (PB<TB>::STEP >> 4), 1);
        wg_commit();
        wg_wait<W3 - 1>();
        if (RP == 3 && dorel) mbar_arrive(rel);
        wgmma160<1, TB>(a1, da + (6144 >> 4), db + (PB<TB>::STEP >> 4), 1);
        wg_commit();
    });
}
template <int TB>
__device__ __forceinline__ void quad_alone(float (&a0)[80], float (&a1)[80], uint32_t base, uint32_t par, uint32_t pbase,
                                           int cont, bool rel0, bool rel1, bool leader) {
    const uint64_t da0 = mkdesc<16, 1024, 1>(sb) + base * (PR_BYTES >> 4);
    const uint64_t db0 = mkdesc<PB<TB>::LBO, 512, 2>(sb + 8192) + base * (PR_BYTES >> 4);
    static_for<4>([&](auto I) {
        constexpr uint32_t i = I.value;
        const uint64_t da = da0 + i * (PR_BYTES >> 4), db = db0 + i * (PR_BYTES >> 4);
        const int acc = i == 0 ? cont : 1;
        mbar_wait(sb + B_PRFULL + 8 * i + 8 * base, par);
        wg_fence();
        wgmma160<1, TB>(a0, da, db, acc);
        wgmma160<1, TB>(a1, da + (4096 >> 4), db, acc);
        wgmma160<1, TB>(a0, da + (2048 >> 4), db + (PB<TB>::STEP >> 4), 1);
        wgmma160<1, TB>(a1, da + (6144 >> 4), db + (PB<TB>::STEP >> 4), 1);
        wg_commit();
        wg_wait<2>();
        if (leader && (i == 0 ? rel0 : (i == 1 ? rel1 : true)))
            mbar_arrive(sb + B_PREMPTY + 8 * ((i + 2) & 3) + 8 * (i < 2 ? pbase : base));
    });
}
#define PW 1222
#define HP 2
#define LSPLIT 1
#define NPRE 2
#define PWT 4
#define PWQ 2
#define PWO0 1222
#define WO_PF_END 24
#define PWSW 40
#define KVMAX 4

constexpr float QSCALE = 0.08838834764831845f * 1.4426950408889634f;

__device__ __forceinline__ float rbf(float x) { return __uint_as_float(pack_bf16(x, 0.f) << 16); }

__device__ __noinline__ void slow_head(const __nv_bfloat16* xp, const __nv_bfloat16* wp, const __nv_bfloat16* kp,
                                       const __nv_bfloat16* vp, unsigned char* os, int warp, int lane) {
    for (int qn = warp; qn < SQ; qn += 4) {
        float q[4] = {0.f, 0.f, 0.f, 0.f}, o[4] = {0.f, 0.f, 0.f, 0.f};
#pragma unroll 8
        for (int k = 0; k < 1024; k++) {
            const float xv = __bfloat162float(xp[qn * 1024 + k]);
            const uint2 w = __ldg(reinterpret_cast<const uint2*>(wp + (size_t)k * 4096 + 4 * lane));
            q[0] += xv * __uint_as_float(w.x << 16);
            q[1] += xv * __uint_as_float(w.x & 0xffff0000u);
            q[2] += xv * __uint_as_float(w.y << 16);
            q[3] += xv * __uint_as_float(w.y & 0xffff0000u);
        }
#pragma unroll
        for (int u = 0; u < 4; u++) q[u] = rbf(q[u]);
        float m = -INFINITY, l = 0.f;
        for (int key = 0; key < SK; key += 4) {
            float s[4];
            uint2 vv[4];
#pragma unroll
            for (int u = 0; u < 4; u++) {
                const uint2 kk = __ldg(reinterpret_cast<const uint2*>(kp + (key + u) * 128 + 4 * lane));
                vv[u] = __ldg(reinterpret_cast<const uint2*>(vp + (key + u) * 128 + 4 * lane));
                s[u] = q[0] * __uint_as_float(kk.x << 16) + q[1] * __uint_as_float(kk.x & 0xffff0000u) +
                       q[2] * __uint_as_float(kk.y << 16) + q[3] * __uint_as_float(kk.y & 0xffff0000u);
            }
#pragma unroll
            for (int off = 16; off; off >>= 1) {
#pragma unroll
                for (int u = 0; u < 4; u++) s[u] += __shfl_xor_sync(0xffffffffu, s[u], off);
            }
#pragma unroll
            for (int u = 0; u < 4; u++) s[u] = rbf(rbf(s[u]) * 0.08838834764831845f) * 1.4426950408889634f;
            const float mn = fmaxf(fmaxf(m, fmaxf(s[0], s[1])), fmaxf(s[2], s[3]));
            const float mref = (mn == -INFINITY) ? 0.f : mn;
            const float corr = exp2f(m - mref);
            m = mn;
            l *= corr;
            o[0] *= corr; o[1] *= corr; o[2] *= corr; o[3] *= corr;
#pragma unroll
            for (int u = 0; u < 4; u++) {
                const float pw = exp2f(s[u] - mref);
                l += pw;
                o[0] += pw * __uint_as_float(vv[u].x << 16);
                o[1] += pw * __uint_as_float(vv[u].x & 0xffff0000u);
                o[2] += pw * __uint_as_float(vv[u].y << 16);
                o[3] += pw * __uint_as_float(vv[u].y & 0xffff0000u);
            }
        }
        const float inv = 1.f / l;
#pragma unroll
        for (int u = 0; u < 4; u++) {
            const int d = 4 * lane + u;
            unsigned short* a = reinterpret_cast<unsigned short*>(
                os + (d >> 5) * 10240 + (qn >> 5) * 2048 + (d & 31) * 64 + ((((qn & 31) >> 3) ^ ((d & 7) >> 1)) << 4) + (qn & 7) * 2);
            *a = (unsigned short)(pack_bf16(o[u] * inv, 0.f) & 0xffffu);
        }
    }
}

#define CTA_COORDS()                                   \
    int cta;                                           \
    asm volatile("mov.u32 %0, %ctaid.x;" : "=r"(cta)); \
    const int g = cta >> 3, j = cta & 7, br = cta >> 6, b = g & 7; \
    (void)g; (void)j; (void)br; (void)b

__global__ void __launch_bounds__(512, 1) mha_fused_kernel(const __grid_constant__ Params prm) {
    extern __shared__ __align__(1024) unsigned char smem_raw[];
    if ((uint32_t)__cvta_generic_to_shared(smem_raw) != sb) __trap();
    const int wg = __shfl_sync(0xffffffffu, threadIdx.x >> 7, 0);
    const int lane = threadIdx.x & 31;

    if ((threadIdx.x >> 5) == 2) {
        if (elect_one()) {
            CTA_COORDS();
#pragma unroll
            for (int i = 0; i < 12; i++) mbar_init(sb + B_PRFULL + 8 * i, 1);
            asm volatile("fence.mbarrier_init.release.cluster;" ::: "memory");
            asm volatile("fence.proxy.async.shared::cta;" ::: "memory");
#pragma unroll 1
            for (int n = 0; n < NPRE; n++) {
                const uint32_t s = (8 - (n & 12)) + (n & 3);
                mbar_expect(sb + B_PRFULL + 8 * s, PR_BYTES);
                tma3(sb + s * PR_BYTES, &prm.wq[br], 0, n * 32, 2 * j, sb + B_PRFULL + 8 * s);
                tma2(sb + s * PR_BYTES + 8192, &prm.x[br], n * 32, b * SQ, sb + B_PRFULL + 8 * s);
            }
        }
        __syncwarp();
    } else if (threadIdx.x >= 128 && lane < 8) {
        const uint32_t a = SM_BAR + 8 * ((threadIdx.x >> 5) - 4 + 12 * lane);
        const bool one = a < B_KEMPTY || (a >= B_VFULL && a < B_VEMPTY) || (a >= B_QFULL && a < B_QREADY) ||
                         (a >= B_QVIS && a < B_PREMPTY) || (a >= B_ORDY && a < B_KVGO);
        if (a < B_PRFULL || a >= B_PREMPTY) mbar_init(sb + a, one ? 1 : 4);
        asm volatile("fence.mbarrier_init.release.cluster;" ::: "memory");
        asm volatile("fence.proxy.async.shared::cta;" ::: "memory");
    }
    __syncthreads();
    if (wg == 1) { TR(7, 0); TRG(7, 1); }

    if (wg == 0) {
        asm volatile("setmaxnreg.dec.sync.aligned.u32 24;");
        const int warp = __shfl_sync(0xffffffffu, warp_now(), 0);
        if (warp == 0) {
            if (elect_one()) {
                CTA_COORDS();
                const int row0 = (b * NH + j) * SK;
                mbar_wait(sb + B_KVGO, 0);
#pragma unroll 1
                for (int t = 0; t < 65; t++) {
                    if (t < 64) {
                        const uint32_t s = t & 1;
                        const bool newq = (t & 15) == 1 && t > 1;
                        const unsigned char* qsrc = g_scr + (size_t)(g * 32 + ((t >> 4) - 1) * 8 + j) * 40960;
                        if (newq) {
                            mbar_wait(sb + B_QVIS + 8 * (t >> 4), 0);
                            mbar_wait(sb + B_QFREE, ((t >> 4) & 1) ^ 1);
                            mbar_expect(sb + B_QFULL, 20480);
                            bulk_g2s(sb + SM_Q, qsrc, 20480, sb + B_QFULL);
                        }
                        mbar_wait(sb + B_KEMPTY + 8 * s, ((t >> 1) & 1) ^ 1);
                        if (newq) {
                            mbar_expect(sb + B_QFULL + 8, 20480);
                            bulk_g2s(sb + SM_Q + 20480, qsrc + 20480, 20480, sb + B_QFULL + 8);
                        }
                        mbar_expect(sb + B_KFULL + 8 * s, 16384);
                        tma3_hint(sb + SM_K + s * 16384, &prm.k[br], 0, row0 + (t >> 4) * (8 * SK) + (t & 15) * 64, 0,
                                  sb + B_KFULL + 8 * s, POL_EF);
                    }
                    if (t == 1) mbar_wait(sb + B_KVGO + 8, 0);
#pragma unroll 1
                    for (int u = t == 2 ? 2 : t - 1; u >= 0 && u < (t == 1 ? 2 : t); u++) {
                        const uint32_t s = u & 1;
                        mbar_wait(sb + B_VEMPTY + 8 * s, ((u >> 1) & 1) ^ 1);
                        mbar_expect(sb + B_VFULL + 8 * s, 16384);
                        tma3_hint(sb + SM_V + s * 16384, &prm.v[br], 0, row0 + (u >> 4) * (8 * SK) + (u & 15) * 64, 0,
                                  sb + B_VFULL + 8 * s, POL_EF);
                    }
                }
            }
        } else if (warp == 1) {
            if (lane == 0) {
                CTA_COORDS();
                const unsigned int target = g_epoch[cta] + 1;
#pragma unroll 1
                for (int r = 0; r < 4; r++) {
                    mbar_wait(sb + B_ODONE + 8 * r, 0);
                    asm volatile("st.release.gpu.global.u32 [%0], %1;" ::"l"(g_flag + g * 32 + r * 8 + j), "r"(target) : "memory");
                    TR(3, 10 + r);
                }
            }
        } else if (warp == 2) {
            if (elect_one()) {
                CTA_COORDS();
                int pf = 8 + (b >> 2);
#pragma unroll 1
                for (int n = NPRE; n < 12; n++) {
                    const uint32_t s = (8 - (n & 12)) + (n & 3);
                    mbar_expect(sb + B_PRFULL + 8 * s, PR_BYTES);
                    tma3(sb + s * PR_BYTES, &prm.wq[br], 0, n * 32, 2 * j, sb + B_PRFULL + 8 * s);
                    tma2(sb + s * PR_BYTES + 8192, &prm.x[br], n * 32, b * SQ, sb + B_PRFULL + 8 * s);
                }
#pragma unroll 1
                for (int q = 3; q < 32; q++) {
                    uint32_t base, par;
                    pr_quad(q, base, par);
                    const uint32_t dst = sb + base * PR_BYTES, bar = sb + B_PRFULL + 8 * base;
                    const int k0 = (q & 7) * 128, hc = 2 * ((q >> 3) * 8 + j);
#pragma unroll
                    for (int i = 0; i < 4; i++) {
                        mbar_wait(bar + (B_PREMPTY - B_PRFULL) + 8 * i, par ^ 1);
                        mbar_expect(bar + 8 * i, PR_BYTES);
                        tma3(dst + i * PR_BYTES, &prm.wq[br], 0, k0 + i * 32, hc, bar + 8 * i);
                        tma2(dst + i * PR_BYTES + 8192, &prm.x[br], k0 + i * 32, b * SQ, bar + 8 * i);
                    }
                    const int mend = q <= 8 ? 8 + HP * (q - 2) : q + PDQ + 1;
                    for (; pf < mend; pf += 2) {
                        if (pf < 32) pf3(&prm.wq[br], 0, (pf & 7) * 128 + (b & 3) * 32, 2 * ((pf >> 3) * 8 + j));
                        else pf3(&prm.wo[br], 0, (pf - 32) * 128 + (b & 3) * 32, 2 * j);
                    }
                }
                const unsigned char* osrc = g_scr + (size_t)g * (128 * 10240);
#pragma unroll 1
                for (int q = 0; q < 32; q++) {
                    uint32_t base, par;
                    pr_quad(32 + q, base, par);
                    const uint32_t dst = sb + base * PR_BYTES, bar = sb + B_PRFULL + 8 * base;
                    if (32 + q == TQ + 1) mbar_wait(sb + B_ADONE, 0);
                    mbar_wait(sb + B_ORDY + 8 * q, 0);
                    uint32_t hh;
                    asm volatile("ld.shared.u8 %0, [%1];" : "=r"(hh) : "r"(sb + SM_ORD + q) : "memory");
#pragma unroll
                    for (int i = 0; i < 4; i++) {
                        mbar_wait(bar + (B_PREMPTY - B_PRFULL) + 8 * i, par ^ 1);
                        mbar_expect(bar + 8 * i, PR_BYTES);
                        tma3(dst + i * PR_BYTES, &prm.wo[br], 0, hh * 128 + i * 32, 2 * j, bar + 8 * i);
                        bulk_g2s(dst + i * PR_BYTES + 8192, osrc + hh * 40960 + i * 10240, 10240, bar + 8 * i);
                    }
                    const int m = q + PDQ;
                    if (m < WO_PF_END && (m & 1) == (b >> 2)) pf3(&prm.wo[br], 0, m * 128 + (b & 3) * 32, 2 * j);
                }
            }
        } else {
            CTA_COORDS();
            const unsigned int target = g_epoch[cta] + 1;
            if (lane == 0) {
#pragma unroll 1
                for (int r = 1; r < 4; r++) {
                    mbar_wait(sb + B_QREADY + 8 * r, 0);
                    asm volatile("fence.acq_rel.gpu;" ::: "memory");
                    asm volatile("fence.proxy.async.global;" ::: "memory");
                    mbar_arrive(sb + B_QVIS + 8 * r);
                    if (r == 2) break;
                }
            }
            __syncwarp();
            int nr = 0;
            unsigned int seen = 0;
            bool q3 = false;
            unsigned int it = 0;
            while (nr < 32) {
                if (!q3 && mbar_test(sb + B_QREADY + 24, 0)) {
                    if (lane == 0) {
                        asm volatile("fence.acq_rel.gpu;" ::: "memory");
                        asm volatile("fence.proxy.async.global;" ::: "memory");
                        mbar_arrive(sb + B_QVIS + 24);
                    }
                    q3 = true;
                }
                unsigned int v;
                asm volatile("ld.acquire.gpu.global.u32 %0, [%1];" : "=r"(v) : "l"(g_flag + g * 32 + lane) : "memory");
                const unsigned int fresh = __ballot_sync(0xffffffffu, v == target) & ~seen;
                if (fresh) {
                    asm volatile("fence.proxy.async.global;" ::: "memory");
                    if ((fresh >> lane) & 1) {
                        const uint32_t pos = nr + __popc(fresh & ((1u << lane) - 1));
                        asm volatile("st.shared.u8 [%0], %1;" ::"r"(sb + SM_ORD + pos), "r"(lane) : "memory");
                        mbar_arrive(sb + B_ORDY + 8 * pos);
                    }
                    nr += __popc(fresh);
                    seen |= fresh;
                }
                if (nr < 24) __nanosleep(400);
                else if (!mbar_test(sb + B_ADONE, 0)) __nanosleep(150);
                if (++it > 33554432u) __trap();
                __syncwarp();
            }
            if (lane == 0) g_epoch[cta] = target;
        }
    } else if (wg == 1) {
        asm volatile("setmaxnreg.dec.sync.aligned.u32 104;");
        float s[40], x[40];
#pragma unroll
        for (int i = 0; i < 40; i++) s[i] = x[i] = 0.f;
        const uint32_t t8 = lane & 7, m = lane >> 3;
        const uint32_t pst = sb + SM_P + (8 * (m >> 1) + t8) * 128 + (((2 * warp_now() + (m & 1)) ^ t8) << 4);
        auto qk = [&](uint32_t sl, int hf) {
            const uint64_t da = mkdesc<16, 1024, 1>(sb + SM_K + sl * 16384);
            const uint64_t db = mkdesc<4096, 256, 3>(sb + SM_Q + hf * 20480);
            wg_fence();
#pragma unroll
            for (int kk = 0; kk < 8; kk++)
                wgmma80<0, 1>(s, da + (((kk >> 2) * 8192 + (kk & 3) * 32) >> 4), db + ((kk * 512) >> 4), kk != 0 ? 1 : prm.zero);
            wg_commit();
        };
        auto expo = [&](uint32_t pa, int jj) {
            stsm4t(pa + jj * 2048, pack_bf16(ex2(x[8 * jj]), ex2(x[8 * jj + 1])), pack_bf16(ex2(x[8 * jj + 2]), ex2(x[8 * jj + 3])),
                   pack_bf16(ex2(x[8 * jj + 4]), ex2(x[8 * jj + 5])), pack_bf16(ex2(x[8 * jj + 6]), ex2(x[8 * jj + 7])));
        };
        auto stage = [&]() {
            wg_wait<0>();
            acc_fence(s);
#pragma unroll
            for (int i = 0; i < 40; i++) x[i] = s[i] * QSCALE;
            acc_fence(x);
        };
        mbar_wait(sb + B_QREADY, 0);
        mbar_wait(sb + B_KFULL, 0);
        qk(0, 0);
#pragma unroll 1
        for (int t2 = 0; t2 < 32; t2++) {
            const uint32_t ph = t2 & 1;
            static_for<2>([&](auto SL) {
                constexpr uint32_t sl = SL.value;
                const uint32_t pa = pst + sl * P_BYTES;
                TR(0, (2 * t2 + sl) * 5);
                if (sl == 0 && (t2 & 3) == 0) TRG(6, 2 * t2);
                stage();
                mbar_wait(sb + B_PEMPTY + 8 * sl, ph ^ 1);
                if (sl == 0 && (t2 & 7) == 0 && t2 != 0) mbar_wait(sb + B_QFULL + 8, ((t2 >> 3) & 1) ^ 1);
                TR2(0, (2 * t2 + sl) * 5 + 1);
                qk(sl, 1);
                if (QGA >= 1) expo(pa, 0);
                if (QGA >= 2) expo(pa, 1);
                SCHED_FENCE(t2, sl);
                if (QGA < 1) expo(pa, 0);
                if (QGA < 2) expo(pa, 1);
                expo(pa, 2);
                expo(pa, 3);
                wg_wait<0>();
                mbar_arrive_warp(sb + B_KEMPTY + 8 * sl);
                expo(pa, 4);
                TR2(0, (2 * t2 + sl) * 5 + 2);
                stage();
                TR2(0, (2 * t2 + sl) * 5 + 3);
                const bool last = sl == 1 && (t2 & 7) == 7;
                if (!last) {
                    mbar_wait(sb + B_KFULL + 8 * (sl ^ 1), sl == 0 ? ph : ph ^ 1);
                    qk(sl ^ 1, 0);
                    if (QGB >= 1) expo(pa + 10240, 0);
                    if (sl == 0) SCHED_FENCE(t2, 2);
                } else {
                    if (QGB >= 1) expo(pa + 10240, 0);
                }
                if (QGB < 1) expo(pa + 10240, 0);
                expo(pa + 10240, 1);
                expo(pa + 10240, 2);
                if (sl == 0 && (t2 & 7) == 7) {
                    wg_wait<0>();
                    mbar_arrive_warp(sb + B_QFREE);
                }
                expo(pa + 10240, 3);
                expo(pa + 10240, 4);
                asm volatile("fence.acq_rel.cta;" ::: "memory");
                __syncwarp();
                mbar_arrive_warp(sb + B_PFULL + 8 * sl);
                if (last && t2 != 31) {
                    mbar_wait(sb + B_QFULL, (t2 >> 3) & 1);
                    mbar_wait(sb + B_KFULL, ph ^ 1);
                    qk(0, 0);
                }
                TR2(0, (2 * t2 + sl) * 5 + 4);
            });
        }
        wg_wait<0>();
    } else if (wg == 2) {
        asm volatile("setmaxnreg.inc.sync.aligned.u32 192;");
        float o0[80], o1[80];
        const uint32_t prow = warp_now() * 8 + (lane >> 2);
        const uint32_t pld = prow * 128 + (((lane & 3) | ((prow & 1) << 2)) << 4);
#pragma unroll 1
        for (int r = 0; r < 4; r++) {
            float l[5] = {0.f, 0.f, 0.f, 0.f, 0.f};
            bool bad = false;
            auto pv_begin = [&](auto SL, auto ACC, uint32_t ph) {
                constexpr uint32_t sl = SL.value;
                mbar_wait(sb + B_VFULL + 8 * sl, ph);
                mbar_wait(sb + B_PFULL + 8 * sl, ph);
                asm volatile("fence.proxy.async.shared::cta;" ::: "memory");
                wg_fence();
                wgmma160<1, 0>(o0, mkdesc<16, 1024, 1>(sb + SM_V + sl * 16384), mkdesc<16, 1024, 1>(sb + SM_P + sl * P_BYTES), ACC.value);
                wg_commit();
                wgmma160<1, 0>(o1, mkdesc<16, 1024, 1>(sb + SM_V + sl * 16384 + 8192), mkdesc<16, 1024, 1>(sb + SM_P + sl * P_BYTES), ACC.value);
                wg_commit();
            };
            pv_begin(IC<0>{}, IC<0>{}, 0);
#pragma unroll 1
            for (int i2 = 0; i2 < 8; i2++) static_for<2>([&](auto SL) {
                constexpr uint32_t sl = SL.value;
                const uint64_t da = mkdesc<16, 1024, 1>(sb + SM_V + sl * 16384);
                const uint64_t db = mkdesc<16, 1024, 1>(sb + SM_P + sl * P_BYTES);
                if (sl == 0) wg_fence();
                uint32_t w[8];
                static_for<8, 2>([&](auto K) {
                    constexpr int k = K.value;
                    if constexpr (k >= PVW) wg_wait<PVW - 1>();
                    if constexpr (k >= 4) wg_fence();
                    if (k & 1) wgmma160<1, 0>(o1, da + ((8192 + (k >> 1) * 2048) >> 4), db + (((k >> 1) * 32) >> 4), 1);
                    else wgmma160<1, 0>(o0, da + (((k >> 1) * 2048) >> 4), db + (((k >> 1) * 32) >> 4), 1);
                    wg_commit();
                    if constexpr (k >= 4) lsum(l[k - 4], w);
                    if constexpr (k >= 3) {
                        lds128u<sb + SM_P + sl * P_BYTES + (k - 3) * 4096>(pld, w);
                        lds128u<sb + SM_P + sl * P_BYTES + (k - 3) * 4096>(pld ^ 64, w + 4);
                        SCHED_FENCE(i2, k + 8 * sl);
                    }
                });
                lsum(l[4], w);
                if (sl == 1 && i2 == 7) {
#pragma unroll
                    for (int k = 0; k < 5; k++) l[k] += __shfl_xor_sync(0xffffffffu, l[k], 1);
#pragma unroll
                    for (int k = 0; k < 5; k++) l[k] += __shfl_xor_sync(0xffffffffu, l[k], 2);
                    const uint32_t ln = lane_now();
                    const uint32_t la = sb + SM_LINV + (((ln >> 3) & 3) * 8 + warp_now() * 2 + ((ln >> 2) & 1)) * 4;
#pragma unroll
                    for (int k = 0; k < 5; k++) {
                        bad |= !(l[k] >= 0.00390625f && l[k] <= 4294967296.f);
                        float v;
                        asm("rcp.approx.ftz.f32 %0, %1;" : "=f"(v) : "f"(l[k]));
                        if ((ln & 3) == 0) asm volatile("st.shared.f32 [%0], %1;" ::"r"(la + 128 * k), "f"(v) : "memory");
                    }
                }
                wg_wait<0>();
                __syncwarp();
                mbar_arrive_warp(sb + B_PEMPTY + 8 * sl);
                mbar_arrive_warp(sb + B_VEMPTY + 8 * sl);
                if (sl == 0) pv_begin(IC<1>{}, IC<1>{}, i2 & 1);
                else if (i2 != 7) pv_begin(IC<0>{}, IC<1>{}, (i2 & 1) ^ 1);
            });
            wg_wait<0>();
            if (r == 3) mbar_arrive_warp(sb + B_ADONE);
            acc_fence(o0);
            acc_fence(o1);
            TR(4, r * 4);
            uint32_t redo;
            asm volatile("{\n.reg .pred p, q;\nsetp.ne.u32 p, %1, 0;\nbar.red.or.pred q, 1, 128, p;\nselp.u32 %0, 1, 0, q;\n}"
                         : "=r"(redo) : "r"((uint32_t)bad) : "memory");
            TR(4, r * 4 + 1);
            if (r < 3) mbar_wait(sb + B_QFULL, r & 1);
            CTA_COORDS();
            unsigned char* os = g_scr + (size_t)(g * 32 + 8 * r + j) * 40960;
            if (__any_sync(0xffffffffu, redo)) {
                const int h = 8 * r + j;
                if (r < 3) mbar_wait(sb + B_QFULL + 8, r & 1);
                slow_head(prm.xp[br] + (size_t)b * SQ * 1024, prm.wqp[br] + h * 128, prm.kp[br] + (size_t)(b * NH + h) * SK * 128,
                          prm.vp[br] + (size_t)(b * NH + h) * SK * 128, os, warp_now(), lane_now());
            } else {
                const uint32_t ln = lane_now(), g8 = ln >> 2, warp = warp_now();
                unsigned char* op = os + (warp >> 1) * 10240 + (16 * (warp & 1) + g8) * 64 + (((ln & 3) ^ (g8 >> 1)) << 4);
                const uint32_t li = (ln & 3) * 32;
                float iv[40];
                lds128i<sb + SM_LINV>(li, iv);
                lds128i<sb + SM_LINV + 16>(li, iv + 4);
                auto put = [&](const float* o, const float* v, unsigned char* p) {
                    stg128(p, pack_bf16(o[0] * v[0], o[1] * v[1]), pack_bf16(o[4] * v[2], o[5] * v[3]),
                           pack_bf16(o[8] * v[4], o[9] * v[5]), pack_bf16(o[12] * v[6], o[13] * v[7]));
                };
                static_for<5>([&](auto I) {
                    constexpr int i = I.value;
                    if constexpr (i < 4) {
                        lds128i<sb + SM_LINV + 128 * (i + 1)>(li, iv + 8 * (i + 1));
                        lds128i<sb + SM_LINV + 128 * (i + 1) + 16>(li, iv + 8 * (i + 1) + 4);
                    }
                    put(o0 + 16 * i, iv + 8 * i, op + i * 2048);
                    put(o0 + 16 * i + 2, iv + 8 * i, op + i * 2048 + 512);
                });
                if (r < 3) mbar_wait(sb + B_QFULL + 8, r & 1);
                static_for<5>([&](auto I) {
                    constexpr int i = I.value;
                    put(o1 + 16 * i, iv + 8 * i, op + 20480 + i * 2048);
                    put(o1 + 16 * i + 2, iv + 8 * i, op + 20480 + i * 2048 + 512);
                });
            }
            TR(4, r * 4 + 2);
            __syncwarp();
            mbar_arrive_warp(sb + B_ODONE + 8 * r);
            TR(3, r);
        }
    } else {
        asm volatile("setmaxnreg.inc.sync.aligned.u32 192;");
        float a0[80], a1[80];
        const bool leader = lane == 0;
        {
            uint32_t pbase = 0;
#pragma unroll 1
            for (int q = 0; q < 8; q++) {
                uint32_t base, par;
                pr_quad(q, base, par);
                if (leader && q == K_START) mbar_arrive(sb + B_KVGO);
                if (leader && q == V_START) mbar_arrive(sb + B_KVGO + 8);
                quad_alone<0>(a0, a1, base, par, pbase, q, q != 0, q != 0, leader);
                TR(2, q);
                pbase = base;
            }
            const uint32_t ln = lane_now(), g8 = ln >> 2;
            const uint32_t qo = ((ln >> 1) & 1) * 4096 + (16 * warp_now() + g8) * 32 + (((ln & 1) ^ (g8 >> 2)) << 4);
            wg_wait<0>();
            acc_fence(a0);
            acc_fence(a1);
            TR(4, 16);
            if (leader) {
                mbar_arrive(sb + B_PREMPTY + 8 * 6);
                mbar_arrive(sb + B_PREMPTY + 8 * 7);
            }
            asm volatile("bar.sync 2, 128;" ::: "memory");
            static_for<20>([&](auto I) {
                constexpr int i = I.value, a = 16 * (i >> 2) + 2 * (i & 1);
                const float* v = (i & 2) ? a1 : a0;
                sts128i<sb + SM_Q + (i >> 2) * 8192 + ((i >> 1) & 1) * 2048 + (i & 1) * 256>(
                    qo, pack_bf16(v[a], v[a + 1]), pack_bf16(v[a + 4], v[a + 5]), pack_bf16(v[a + 8], v[a + 9]),
                    pack_bf16(v[a + 12], v[a + 13]));
            });
            asm volatile("fence.proxy.async.shared::cta;" ::: "memory");
            __syncwarp();
            mbar_arrive_warp(sb + B_QREADY);
            TR(3, 4);
        }
#pragma unroll 1
        for (int r = 1; r < 4; r++) {
            quad_shared<PWQ, 0, 0>(a0, a1, 1, leader);
            TR(2, 8 * r);
#pragma unroll 1
            for (int q = 1; q < 8; q++) {
                quad_shared<PWQ, 0>(a0, a1, (q + 1) & 1, leader);
                TR(2, 8 * r + q);
            }
            CTA_COORDS();
            const uint32_t ln = lane_now(), g8 = ln >> 2;
            unsigned char* qp = g_scr + (size_t)(g * 32 + (r - 1) * 8 + j) * 40960 + ((ln >> 1) & 1) * 4096 +
                                (16 * warp_now() + g8) * 32 + (((ln & 1) ^ (g8 >> 2)) << 4);
            wg_wait<0>();
            acc_fence(a0);
            acc_fence(a1);
            TR(4, 16 + r);
            mbar_arrive_warp(sb + B_PREMPTY + 8 * 3);
#pragma unroll
            for (int i = 0; i < 20; i++) {
                const int a = 16 * (i >> 2) + 2 * (i & 1);
                const float* v = (i & 2) ? a1 : a0;
                stg128(qp + (i >> 2) * 8192 + ((i >> 1) & 1) * 2048 + (i & 1) * 256, pack_bf16(v[a], v[a + 1]),
                       pack_bf16(v[a + 4], v[a + 5]), pack_bf16(v[a + 8], v[a + 9]), pack_bf16(v[a + 12], v[a + 13]));
            }
            __syncwarp();
            mbar_arrive_warp(sb + B_QREADY + 8 * r);
            TR(3, 4 + r);
        }
        bool alone = false;
        quad_shared<PWO0, 1, 0>(a0, a1, 1, leader);
        TR(2, 32);
#pragma unroll 1
        for (int q = 33; q <= (TQ < 63 ? TQ : 62); q++) {
            if (!alone && q >= 44) {
                uint32_t a;
                asm volatile("{\n.reg .pred p, q;\nmbarrier.test_wait.parity.shared::cta.b64 p, [%1], 0;\n"
                             "bar.red.and.pred q, 2, 128, p;\nselp.u32 %0, 1, 0, q;\n}" : "=r"(a) : "r"(sb + B_ADONE) : "memory");
                alone = a != 0;
            }
            if (alone) quad_shared<PWT, 1>(a0, a1, (q + 1) & 1, leader);
            else if (PW != PWO0 && q < PWSW) quad_shared<PWO0, 1>(a0, a1, (q + 1) & 1, leader);
            else quad_shared<PW, 1>(a0, a1, (q + 1) & 1, leader);
            TR(2, q);
        }
        {
            uint32_t pbase = 0;
#pragma unroll 1
            for (int q = TQ + 1; q < 63; q++) {
                uint32_t base, par;
                pr_quad(q, base, par);
                quad_alone<1>(a0, a1, base, par, pbase, 1, q != TQ + 1, true, leader);
                TR(2, q);
                pbase = base;
            }
        }
        static_assert((63 - TQ) % 3 == 0, "the last quad sits in slots 0..3");
        const uint32_t ln = lane_now(), t8 = ln & 7, m = ln >> 3, warp = warp_now();
        const uint32_t pst = sb + SM_Q + (8 * (m >> 1) + t8) * 128 + (((2 * warp + (m & 1)) ^ t8) << 4);
        constexpr uint32_t lpar = ((63 - TQ) / 3 + TQ + 1) & 1;
        if (TQ < 63) asm volatile("bar.sync 2, 128;" ::: "memory");
        static_for<4>([&](auto I) {
            constexpr uint32_t i = I.value;
            mbar_wait(sb + B_PRFULL + 8 * i, lpar);
            wg_fence();
            wgmma160<1, 1>(a0, mkdesc<16, 1024, 1>(sb + i * PR_BYTES), mkdesc<2048, 512, 2>(sb + i * PR_BYTES + 8192), 1);
            wgmma160<1, 1>(a0, mkdesc<16, 1024, 1>(sb + i * PR_BYTES + 2048), mkdesc<2048, 512, 2>(sb + i * PR_BYTES + 9216), 1);
            if (i < LSPLIT) {
                wgmma160<1, 1>(a1, mkdesc<16, 1024, 1>(sb + i * PR_BYTES + 4096), mkdesc<2048, 512, 2>(sb + i * PR_BYTES + 8192), 1);
                wgmma160<1, 1>(a1, mkdesc<16, 1024, 1>(sb + i * PR_BYTES + 6144), mkdesc<2048, 512, 2>(sb + i * PR_BYTES + 9216), 1);
            }
            wg_commit();
            if (TQ == 63 && i == 0) {
                wg_wait<1>();
                if (leader) mbar_arrive(sb + B_PREMPTY + 8 * 3);
            }
        });
        static_for<4, LSPLIT>([&](auto I) {
            constexpr uint32_t i = I.value;
            wgmma160<1, 1>(a1, mkdesc<16, 1024, 1>(sb + i * PR_BYTES + 4096), mkdesc<2048, 512, 2>(sb + i * PR_BYTES + 8192), 1);
            wgmma160<1, 1>(a1, mkdesc<16, 1024, 1>(sb + i * PR_BYTES + 6144), mkdesc<2048, 512, 2>(sb + i * PR_BYTES + 9216), 1);
        });
        wg_commit();
        TR(2, 63);
        wg_wait<1>();
        acc_fence(a0);
        TR(4, 20);
#pragma unroll
        for (int jj = 0; jj < 10; jj++)
            stsm4t(pst + jj * 2048, pack_bf16(a0[8 * jj], a0[8 * jj + 1]), pack_bf16(a0[8 * jj + 2], a0[8 * jj + 3]),
                   pack_bf16(a0[8 * jj + 4], a0[8 * jj + 5]), pack_bf16(a0[8 * jj + 6], a0[8 * jj + 7]));
        asm volatile("fence.proxy.async.shared::cta;" ::: "memory");
        asm volatile("bar.sync 2, 128;" ::: "memory");
        if (warp == 0 && elect_one()) {
            CTA_COORDS();
            tma2_store(&prm.out, sb + SM_Q, br * 1024 + j * 128, b * SQ);
            asm volatile("cp.async.bulk.commit_group;" ::: "memory");
        }
        __syncwarp();
        wg_wait<0>();
        acc_fence(a1);
#pragma unroll
        for (int jj = 0; jj < 10; jj++)
            stsm4t(pst + P_BYTES + jj * 2048, pack_bf16(a1[8 * jj], a1[8 * jj + 1]), pack_bf16(a1[8 * jj + 2], a1[8 * jj + 3]),
                   pack_bf16(a1[8 * jj + 4], a1[8 * jj + 5]), pack_bf16(a1[8 * jj + 6], a1[8 * jj + 7]));
        asm volatile("fence.proxy.async.shared::cta;" ::: "memory");
        asm volatile("bar.sync 2, 128;" ::: "memory");
        TR(4, 21);
        if (warp == 0 && elect_one()) {
            CTA_COORDS();
            tma2_store(&prm.out, sb + SM_Q + P_BYTES, br * 1024 + j * 128 + 64, b * SQ);
            asm volatile("cp.async.bulk.commit_group;" ::: "memory");
            asm volatile("cp.async.bulk.wait_group 0;" ::: "memory");
            TR(3, 8);
            TRG(7, 2);
        }
    }
}

typedef CUresult (*EncodeFn)(CUtensorMap*, CUtensorMapDataType, cuuint32_t, void*, const cuuint64_t*, const cuuint64_t*,
                             const cuuint32_t*, const cuuint32_t*, CUtensorMapInterleave, CUtensorMapSwizzle,
                             CUtensorMapL2promotion, CUtensorMapFloatOOBfill);

#define PROMO_W CU_TENSOR_MAP_L2_PROMOTION_L2_128B
#define PROMO_KV CU_TENSOR_MAP_L2_PROMOTION_L2_128B
void encode(EncodeFn fn, CUtensorMap* m, void* p, int rank, const cuuint64_t* dims, const cuuint64_t* strides,
            const cuuint32_t* box, CUtensorMapSwizzle swz, CUtensorMapL2promotion promo = PROMO_W) {
    cuuint32_t es[3] = {1, 1, 1};
    fn(m, CU_TENSOR_MAP_DATA_TYPE_BFLOAT16, rank, p, dims, strides, box, es, CU_TENSOR_MAP_INTERLEAVE_NONE, swz,
       promo, CU_TENSOR_MAP_FLOAT_OOB_FILL_NONE);
}

}

extern "C" void kernel_launch(void* const* d_in, const int* in_sizes, int n_in, void* d_out, int out_size) {
    static EncodeFn fn = nullptr;
    if (!fn) {
        void* f = nullptr;
        cudaDriverEntryPointQueryResult st;
        cudaGetDriverEntryPoint("cuTensorMapEncodeTiled", &f, cudaEnableDefault, &st);
        fn = (EncodeFn)f;
        cudaFuncSetAttribute(mha_fused_kernel, cudaFuncAttributeMaxDynamicSharedMemorySize, SM_TOTAL);
    }
    Params prm;
    prm.zero = 0;
    prm.never = 1 << 20;
    for (int br = 0; br < 2; br++) {
        void* x = d_in[5 * br + 0];
        void* k = d_in[5 * br + 1];
        void* v = d_in[5 * br + 2];
        void* wq = d_in[5 * br + 3];
        void* wo = d_in[5 * br + 4];
        {
            cuuint64_t dims[3] = {64, 8ull * NH * SK, 2}, str[2] = {256, 128};
            cuuint32_t box[3] = {64, 64, 2};
            encode(fn, &prm.k[br], k, 3, dims, str, box, CU_TENSOR_MAP_SWIZZLE_128B, PROMO_KV);
            encode(fn, &prm.v[br], v, 3, dims, str, box, CU_TENSOR_MAP_SWIZZLE_128B, PROMO_KV);
        }
        {
            cuuint64_t dims[3] = {64, 1024, 64}, str[2] = {8192, 128};
            cuuint32_t box[3] = {64, 32, 2};
            encode(fn, &prm.wq[br], wq, 3, dims, str, box, CU_TENSOR_MAP_SWIZZLE_128B);
        }
        {
            cuuint64_t dims[3] = {64, 4096, 16}, str[2] = {2048, 128};
            cuuint32_t box[3] = {64, 32, 2};
            encode(fn, &prm.wo[br], wo, 3, dims, str, box, CU_TENSOR_MAP_SWIZZLE_128B);
        }
        {
            cuuint64_t dims[2] = {1024, 1280}, str[1] = {2048};
            cuuint32_t box[2] = {32, 160};
            encode(fn, &prm.x[br], x, 2, dims, str, box, CU_TENSOR_MAP_SWIZZLE_64B);
        }
        prm.kp[br] = (const __nv_bfloat16*)k;
        prm.vp[br] = (const __nv_bfloat16*)v;
        prm.xp[br] = (const __nv_bfloat16*)x;
        prm.wqp[br] = (const __nv_bfloat16*)wq;
    }
    {
        cuuint64_t dims[2] = {2048, 1280}, str[1] = {4096};
        cuuint32_t box[2] = {64, 160};
        encode(fn, &prm.out, d_out, 2, dims, str, box, CU_TENSOR_MAP_SWIZZLE_128B);
    }
    mha_fused_kernel<<<NCTA, 512, SM_TOTAL, cudaStreamPerThread>>>(prm);
}
```

```cpp
#include <cuda_runtime.h>
#include <cuda_bf16.h>
#include <cuda.h>
#include <stdint.h>

namespace {

constexpr int SQ = 160, SK = 1024, NH = 32;
constexpr int NCTA = 128;

constexpr uint32_t sb = 1024;
constexpr uint32_t PR_BYTES = 18432;
constexpr uint32_t SM_Q = 4 * PR_BYTES;
constexpr uint32_t SM_P = SM_Q + 40960;
constexpr uint32_t P_BYTES = 20480;
constexpr uint32_t SM_K = SM_P + 2 * P_BYTES;
constexpr uint32_t SM_V = SM_K + 2 * 16384;
constexpr uint32_t SM_LINV = SM_V + 2 * 16384;
constexpr uint32_t SM_BAR = SM_LINV + 160 * 4;
constexpr uint32_t SM_ORD = SM_BAR + 768;
constexpr uint32_t SM_TOTAL = SM_ORD + 32;
static_assert(SM_V + 2 * 16384 == 12 * PR_BYTES, "Q/P/K/V double as stage slots 4..11 before and after attention");
constexpr uint32_t B_KFULL = SM_BAR + 0;
constexpr uint32_t B_KEMPTY = SM_BAR + 16;
constexpr uint32_t B_VFULL = SM_BAR + 32;
constexpr uint32_t B_VEMPTY = SM_BAR + 48;
constexpr uint32_t B_PFULL = SM_BAR + 64;
constexpr uint32_t B_PEMPTY = SM_BAR + 80;
constexpr uint32_t B_QFULL = SM_BAR + 96;
constexpr uint32_t B_QREADY = SM_BAR + 112;
constexpr uint32_t B_ODONE = SM_BAR + 144;
constexpr uint32_t B_QVIS = SM_BAR + 176;
constexpr uint32_t B_PRFULL = SM_BAR + 208;
constexpr uint32_t B_PREMPTY = SM_BAR + 304;
constexpr uint32_t B_ORDY = SM_BAR + 400;
constexpr uint32_t B_KVGO = SM_BAR + 656;
constexpr uint32_t B_QFREE = SM_BAR + 672;
constexpr uint32_t B_ADONE = SM_BAR + 680;
constexpr int KV_START = 7;
constexpr int NPRE = 2;
constexpr int PDQ = 5;
constexpr int HP = 2;
constexpr int OCH = 2;
constexpr int PVW = 3;
constexpr int PWQ = 2, PWO = 1222, PWT = 4;

template <int V> struct IC { static constexpr int value = V; };
template <int N, int I = 0, class F> __device__ __forceinline__ void static_for(F&& f) {
    if constexpr (I < N) {
        f(IC<I>{});
        static_for<N, I + 1>(f);
    }
}

struct Params {
    CUtensorMap k[2], v[2], x[2], wq[2], wo[2], out;
    const __nv_bfloat16* kp[2];
    const __nv_bfloat16* vp[2];
    const __nv_bfloat16* xp[2];
    const __nv_bfloat16* wqp[2];
    int zero;
    int never;
};

__device__ __align__(1024) unsigned char g_scr[16 * 32 * 40960];
__device__ __align__(128) unsigned int g_flag[16 * 32];
__device__ unsigned int g_epoch[NCTA];

__device__ __forceinline__ void mbar_init(uint32_t b, int c) {
    asm volatile("mbarrier.init.shared::cta.b64 [%0], %1;" ::"r"(b), "r"(c));
}
__device__ __forceinline__ void mbar_expect(uint32_t b, int bytes) {
    asm volatile("mbarrier.arrive.expect_tx.shared::cta.b64 _, [%0], %1;" ::"r"(b), "r"(bytes) : "memory");
}
__device__ __forceinline__ void mbar_arrive(uint32_t b) {
    asm volatile("mbarrier.arrive.shared::cta.b64 _, [%0];" ::"r"(b) : "memory");
}
__device__ __forceinline__ void mbar_arrive_warp(uint32_t b) {
    asm volatile("{\n.reg .pred p;\nelect.sync _|p, 0xffffffff;\n@p mbarrier.arrive.shared::cta.b64 _, [%0];\n}" ::"r"(b) : "memory");
}
__device__ __forceinline__ bool elect_one() {
    uint32_t r;
    asm volatile("{\n.reg .pred p;\nelect.sync _|p, 0xffffffff;\nselp.u32 %0, 1, 0, p;\n}" : "=r"(r));
    return r != 0;
}
__device__ __forceinline__ uint32_t warp_now() {
    uint32_t r;
    asm volatile("mov.u32 %0, %tid.x;" : "=r"(r));
    return (r >> 5) & 3;
}
__device__ __forceinline__ uint32_t lane_now() {
    uint32_t r;
    asm volatile("mov.u32 %0, %laneid;" : "=r"(r));
    return r;
}
__device__ __forceinline__ void mbar_wait(uint32_t b, uint32_t ph) {
    asm volatile(
        "{\n.reg .pred p;\n.reg .u32 n;\n"
        "mbarrier.try_wait.parity.shared::cta.b64 p, [%0], %1;\n"
        "@p bra D;\n"
        "mov.u32 n, 0;\n"
        "W:\nmbarrier.try_wait.parity.shared::cta.b64 p, [%0], %1;\n"
        "@p bra D;\n"
        "add.u32 n, n, 1;\nsetp.lt.u32 p, n, 4194304;\n@p bra W;\ntrap;\n"
        "D:\n}" ::"r"(b), "r"(ph) : "memory");
}
__device__ __forceinline__ bool mbar_test(uint32_t b, uint32_t ph) {
    uint32_t r;
    asm volatile("{\n.reg .pred p;\nmbarrier.test_wait.parity.shared::cta.b64 p, [%1], %2;\nselp.u32 %0, 1, 0, p;\n}"
                 : "=r"(r) : "r"(b), "r"(ph) : "memory");
    return r != 0;
}
__device__ __forceinline__ void pf3(const CUtensorMap* m, int c0, int c1, int c2) {
    asm volatile("cp.async.bulk.prefetch.tensor.3d.L2.global [%0, {%1, %2, %3}];" ::"l"(m), "r"(c0), "r"(c1), "r"(c2) : "memory");
}
constexpr uint64_t POL_EF = 0x12F0000000000000ull;
__device__ __forceinline__ void tma3(uint32_t dst, const CUtensorMap* m, int c0, int c1, int c2, uint32_t bar) {
    asm volatile("cp.async.bulk.tensor.3d.shared::cluster.global.mbarrier::complete_tx::bytes [%0], [%1, {%3, %4, %5}], [%2];"
                 ::"r"(dst), "l"(m), "r"(bar), "r"(c0), "r"(c1), "r"(c2) : "memory");
}
__device__ __forceinline__ void tma3_hint(uint32_t dst, const CUtensorMap* m, int c0, int c1, int c2, uint32_t bar, uint64_t pol) {
    asm volatile("cp.async.bulk.tensor.3d.shared::cluster.global.mbarrier::complete_tx::bytes.L2::cache_hint [%0], [%1, {%3, %4, %5}], [%2], %6;"
                 ::"r"(dst), "l"(m), "r"(bar), "r"(c0), "r"(c1), "r"(c2), "l"(pol) : "memory");
}
__device__ __forceinline__ void tma2(uint32_t dst, const CUtensorMap* m, int c0, int c1, uint32_t bar) {
    asm volatile("cp.async.bulk.tensor.2d.shared::cluster.global.mbarrier::complete_tx::bytes [%0], [%1, {%3, %4}], [%2];"
                 ::"r"(dst), "l"(m), "r"(bar), "r"(c0), "r"(c1) : "memory");
}
__device__ __forceinline__ void bulk_g2s(uint32_t dst, const void* src, int bytes, uint32_t bar) {
    asm volatile("cp.async.bulk.shared::cluster.global.mbarrier::complete_tx::bytes [%0], [%1], %2, [%3];"
                 ::"r"(dst), "l"(src), "r"(bytes), "r"(bar) : "memory");
}
__device__ __forceinline__ void tma2_store(const CUtensorMap* m, uint32_t src, int c0, int c1) {
    asm volatile("cp.async.bulk.tensor.2d.global.shared::cta.bulk_group [%0, {%2, %3}], [%1];"
                 ::"l"(m), "r"(src), "r"(c0), "r"(c1) : "memory");
}
__device__ __forceinline__ void wg_fence() { asm volatile("wgmma.fence.sync.aligned;" ::: "memory"); }
__device__ __forceinline__ void wg_commit() { asm volatile("wgmma.commit_group.sync.aligned;" ::: "memory"); }
template <int N> __device__ __forceinline__ void wg_wait() { asm volatile("wgmma.wait_group.sync.aligned %0;" ::"n"(N) : "memory"); }
template <int N> __device__ __forceinline__ void acc_fence(float (&d)[N]) {
#pragma unroll
    for (int i = 0; i < N; i++) asm volatile("" : "+f"(d[i])::"memory");
}
template <uint32_t OFF> __device__ __forceinline__ void sts128i(uint32_t p, uint32_t a, uint32_t b, uint32_t c, uint32_t d) {
    asm volatile("st.shared.v4.u32 [%0+%5], {%1, %2, %3, %4};" ::"r"(p), "r"(a), "r"(b), "r"(c), "r"(d), "n"(OFF) : "memory");
}
template <uint32_t OFF> __device__ __forceinline__ void lds128i(uint32_t p, float* v) {
    asm volatile("ld.shared.v4.f32 {%0, %1, %2, %3}, [%4+%5];" : "=f"(v[0]), "=f"(v[1]), "=f"(v[2]), "=f"(v[3]) : "r"(p), "n"(OFF) : "memory");
}
template <uint32_t OFF> __device__ __forceinline__ void lds128u(uint32_t p, uint32_t* v) {
    asm volatile("ld.shared.v4.u32 {%0, %1, %2, %3}, [%4+%5];" : "=r"(v[0]), "=r"(v[1]), "=r"(v[2]), "=r"(v[3]) : "r"(p), "n"(OFF) : "memory");
}
#define SCHED_FENCE(cnt, k) do { if ((cnt) == prm.never + (int)(k)) { wg_wait<0>(); __trap(); } } while (0)
template <uint32_t LBO, uint32_t SBO, uint32_t SWZ>
__device__ __forceinline__ uint64_t mkdesc(uint32_t addr) {
    uint32_t lo = ((addr & 0x3FFFF) >> 4) | ((LBO >> 4) << 16);
    uint32_t hi = (SBO >> 4) | (SWZ << 30);
    return ((uint64_t)hi << 32) | lo;
}

template <int TA, int TB>
__device__ __forceinline__ void wgmma160(float (&d)[80], uint64_t da, uint64_t db, int scale_d) {
    asm volatile(
        "{\n.reg .pred p;\nsetp.ne.b32 p, %82, 0;\n"
        "wgmma.mma_async.sync.aligned.m64n160k16.f32.bf16.bf16 "
        "{%0, %1, %2, %3, %4, %5, %6, %7, %8, %9, %10, %11, %12, %13, %14, %15, %16, %17, %18, %19, "
        "%20, %21, %22, %23, %24, %25, %26, %27, %28, %29, %30, %31, %32, %33, %34, %35, %36, %37, %38, %39, "
        "%40, %41, %42, %43, %44, %45, %46, %47, %48, %49, %50, %51, %52, %53, %54, %55, %56, %57, %58, %59, "
        "%60, %61, %62, %63, %64, %65, %66, %67, %68, %69, %70, %71, %72, %73, %74, %75, %76, %77, %78, %79}, "
        "%80, %81, p, 1, 1, %83, %84;\n}\n"
        : "+f"(d[0]), "+f"(d[1]), "+f"(d[2]), "+f"(d[3]), "+f"(d[4]), "+f"(d[5]), "+f"(d[6]), "+f"(d[7]),
          "+f"(d[8]), "+f"(d[9]), "+f"(d[10]), "+f"(d[11]), "+f"(d[12]), "+f"(d[13]), "+f"(d[14]), "+f"(d[15]),
          "+f"(d[16]), "+f"(d[17]), "+f"(d[18]), "+f"(d[19]), "+f"(d[20]), "+f"(d[21]), "+f"(d[22]), "+f"(d[23]),
          "+f"(d[24]), "+f"(d[25]), "+f"(d[26]), "+f"(d[27]), "+f"(d[28]), "+f"(d[29]), "+f"(d[30]), "+f"(d[31]),
          "+f"(d[32]), "+f"(d[33]), "+f"(d[34]), "+f"(d[35]), "+f"(d[36]), "+f"(d[37]), "+f"(d[38]), "+f"(d[39]),
          "+f"(d[40]), "+f"(d[41]), "+f"(d[42]), "+f"(d[43]), "+f"(d[44]), "+f"(d[45]), "+f"(d[46]), "+f"(d[47]),
          "+f"(d[48]), "+f"(d[49]), "+f"(d[50]), "+f"(d[51]), "+f"(d[52]), "+f"(d[53]), "+f"(d[54]), "+f"(d[55]),
          "+f"(d[56]), "+f"(d[57]), "+f"(d[58]), "+f"(d[59]), "+f"(d[60]), "+f"(d[61]), "+f"(d[62]), "+f"(d[63]),
          "+f"(d[64]), "+f"(d[65]), "+f"(d[66]), "+f"(d[67]), "+f"(d[68]), "+f"(d[69]), "+f"(d[70]), "+f"(d[71]),
          "+f"(d[72]), "+f"(d[73]), "+f"(d[74]), "+f"(d[75]), "+f"(d[76]), "+f"(d[77]), "+f"(d[78]), "+f"(d[79])
        : "l"(da), "l"(db), "r"(scale_d), "n"(TA), "n"(TB));
}
template <int TA, int TB>
__device__ __forceinline__ void wgmma80(float (&d)[40], uint64_t da, uint64_t db, int scale_d) {
    asm volatile(
        "{\n.reg .pred p;\nsetp.ne.b32 p, %42, 0;\n"
        "wgmma.mma_async.sync.aligned.m64n80k16.f32.bf16.bf16 "
        "{%0, %1, %2, %3, %4, %5, %6, %7, %8, %9, %10, %11, %12, %13, %14, %15, %16, %17, %18, %19, "
        "%20, %21, %22, %23, %24, %25, %26, %27, %28, %29, %30, %31, %32, %33, %34, %35, %36, %37, %38, %39}, "
        "%40, %41, p, 1, 1, %43, %44;\n}\n"
        : "+f"(d[0]), "+f"(d[1]), "+f"(d[2]), "+f"(d[3]), "+f"(d[4]), "+f"(d[5]), "+f"(d[6]), "+f"(d[7]),
          "+f"(d[8]), "+f"(d[9]), "+f"(d[10]), "+f"(d[11]), "+f"(d[12]), "+f"(d[13]), "+f"(d[14]), "+f"(d[15]),
          "+f"(d[16]), "+f"(d[17]), "+f"(d[18]), "+f"(d[19]), "+f"(d[20]), "+f"(d[21]), "+f"(d[22]), "+f"(d[23]),
          "+f"(d[24]), "+f"(d[25]), "+f"(d[26]), "+f"(d[27]), "+f"(d[28]), "+f"(d[29]), "+f"(d[30]), "+f"(d[31]),
          "+f"(d[32]), "+f"(d[33]), "+f"(d[34]), "+f"(d[35]), "+f"(d[36]), "+f"(d[37]), "+f"(d[38]), "+f"(d[39])
        : "l"(da), "l"(db), "r"(scale_d), "n"(TA), "n"(TB));
}
__device__ __forceinline__ uint32_t pack_bf16(float lo, float hi) {
    uint32_t r;
    asm("cvt.rn.bf16x2.f32 %0, %1, %2;" : "=r"(r) : "f"(hi), "f"(lo));
    return r;
}
__device__ __forceinline__ uint32_t hadd2(uint32_t a, uint32_t b) {
    uint32_t r;
    asm("add.rn.bf16x2 %0, %1, %2;" : "=r"(r) : "r"(a), "r"(b));
    return r;
}
__device__ __forceinline__ void lsum(float& l, const uint32_t* w) {
    const uint32_t t = hadd2(hadd2(hadd2(w[0], w[1]), hadd2(w[2], w[3])), hadd2(hadd2(w[4], w[5]), hadd2(w[6], w[7])));
    l += __uint_as_float(t << 16) + __uint_as_float(t & 0xffff0000u);
}
__device__ __forceinline__ float ex2(float x) {
    float r;
    asm("ex2.approx.ftz.f32 %0, %1;" : "=f"(r) : "f"(x));
    return r;
}
__device__ __forceinline__ void stsm4t(uint32_t addr, uint32_t a, uint32_t b, uint32_t c, uint32_t d) {
    asm volatile("stmatrix.sync.aligned.m8n8.x4.trans.shared.b16 [%0], {%1, %2, %3, %4};"
                 ::"r"(addr), "r"(a), "r"(b), "r"(c), "r"(d) : "memory");
}
__device__ __forceinline__ void stg128(void* p, uint32_t a, uint32_t b, uint32_t c, uint32_t d) {
    asm volatile("st.global.v4.u32 [%0], {%1, %2, %3, %4};" ::"l"(p), "r"(a), "r"(b), "r"(c), "r"(d) : "memory");
}

template <int TB> struct PB;
template <> struct PB<0> { static constexpr uint32_t LBO = 16, STEP = 32; };
template <> struct PB<1> { static constexpr uint32_t LBO = 2048, STEP = 1024; };

template <int W, int TB, int cont = 1>
__device__ __forceinline__ void quad_shared(float (&a0)[80], float (&a1)[80], uint32_t par, bool leader, bool rel0 = true) {
    static_for<4>([&](auto I) {
        constexpr uint32_t i = I.value;
        constexpr uint32_t rel = sb + B_PREMPTY + 8 * ((i + 3) & 3);
        const uint64_t da = mkdesc<16, 1024, 1>(sb + i * PR_BYTES);
        const uint64_t db = mkdesc<PB<TB>::LBO, 512, 2>(sb + i * PR_BYTES + 8192);
        constexpr int acc = i == 0 ? cont : 1;
        const bool dorel = leader && (i != 0 || (cont && rel0));
        constexpr int W0 = W < 10 ? W : W / 1000, W1 = W < 10 ? W : W / 100 % 10, W2 = W < 10 ? W : W / 10 % 10, W3 = W % 10;
        constexpr int RP = W0 <= 1 ? 0 : (W1 <= 2 ? 1 : (W2 <= 3 ? 2 : 3));
        mbar_wait(sb + B_PRFULL + 8 * i, par);
        wg_wait<W0 - 1>();
        if (RP == 0 && dorel) mbar_arrive(rel);
        wg_fence();
        wgmma160<1, TB>(a0, da, db, acc);
        wg_commit();
        wg_wait<W1 - 1>();
        if (RP == 1 && dorel) mbar_arrive(rel);
        wgmma160<1, TB>(a1, da + (4096 >> 4), db, acc);
        wg_commit();
        wg_wait<W2 - 1>();
        if (RP == 2 && dorel) mbar_arrive(rel);
        wgmma160<1, TB>(a0, da + (2048 >> 4), db + (PB<TB>::STEP >> 4), 1);
        wg_commit();
        wg_wait<W3 - 1>();
        if (RP == 3 && dorel) mbar_arrive(rel);
        wgmma160<1, TB>(a1, da + (6144 >> 4), db + (PB<TB>::STEP >> 4), 1);
        wg_commit();
    });
}
__device__ __forceinline__ void quad_alone(float (&a0)[80], float (&a1)[80], uint32_t base, uint32_t par, uint32_t pbase,
                                           int cont, bool leader) {
    const uint64_t da0 = mkdesc<16, 1024, 1>(sb) + base * (PR_BYTES >> 4);
    const uint64_t db0 = mkdesc<16, 512, 2>(sb + 8192) + base * (PR_BYTES >> 4);
    static_for<4>([&](auto I) {
        constexpr uint32_t i = I.value;
        const uint64_t da = da0 + i * (PR_BYTES >> 4), db = db0 + i * (PR_BYTES >> 4);
        const int acc = i == 0 ? cont : 1;
        mbar_wait(sb + B_PRFULL + 8 * i + 8 * base, par);
        wg_fence();
        wgmma160<1, 0>(a0, da, db, acc);
        wgmma160<1, 0>(a1, da + (4096 >> 4), db, acc);
        wgmma160<1, 0>(a0, da + (2048 >> 4), db + (32 >> 4), 1);
        wgmma160<1, 0>(a1, da + (6144 >> 4), db + (32 >> 4), 1);
        wg_commit();
        wg_wait<2>();
        if (leader && (i >= 2 || cont)) mbar_arrive(sb + B_PREMPTY + 8 * ((i + 2) & 3) + 8 * (i < 2 ? pbase : base));
    });
}

constexpr float QSCALE = 0.08838834764831845f * 1.4426950408889634f;

__device__ __forceinline__ float rbf(float x) { return __uint_as_float(pack_bf16(x, 0.f) << 16); }

__device__ __noinline__ void slow_head(const __nv_bfloat16* xp, const __nv_bfloat16* wp, const __nv_bfloat16* kp,
                                       const __nv_bfloat16* vp, unsigned char* os, int warp, int lane) {
    for (int qn = warp; qn < SQ; qn += 4) {
        float q[4] = {0.f, 0.f, 0.f, 0.f}, o[4] = {0.f, 0.f, 0.f, 0.f};
#pragma unroll 8
        for (int k = 0; k < 1024; k++) {
            const float xv = __bfloat162float(xp[qn * 1024 + k]);
            const uint2 w = __ldg(reinterpret_cast<const uint2*>(wp + (size_t)k * 4096 + 4 * lane));
            q[0] += xv * __uint_as_float(w.x << 16);
            q[1] += xv * __uint_as_float(w.x & 0xffff0000u);
            q[2] += xv * __uint_as_float(w.y << 16);
            q[3] += xv * __uint_as_float(w.y & 0xffff0000u);
        }
#pragma unroll
        for (int u = 0; u < 4; u++) q[u] = rbf(q[u]);
        float m = -INFINITY, l = 0.f;
        for (int key = 0; key < SK; key += 4) {
            float s[4];
            uint2 vv[4];
#pragma unroll
            for (int u = 0; u < 4; u++) {
                const uint2 kk = __ldg(reinterpret_cast<const uint2*>(kp + (key + u) * 128 + 4 * lane));
                vv[u] = __ldg(reinterpret_cast<const uint2*>(vp + (key + u) * 128 + 4 * lane));
                s[u] = q[0] * __uint_as_float(kk.x << 16) + q[1] * __uint_as_float(kk.x & 0xffff0000u) +
                       q[2] * __uint_as_float(kk.y << 16) + q[3] * __uint_as_float(kk.y & 0xffff0000u);
            }
#pragma unroll
            for (int off = 16; off; off >>= 1) {
#pragma unroll
                for (int u = 0; u < 4; u++) s[u] += __shfl_xor_sync(0xffffffffu, s[u], off);
            }
#pragma unroll
            for (int u = 0; u < 4; u++) s[u] = rbf(rbf(s[u]) * 0.08838834764831845f) * 1.4426950408889634f;
            const float mn = fmaxf(fmaxf(m, fmaxf(s[0], s[1])), fmaxf(s[2], s[3]));
            const float mref = (mn == -INFINITY) ? 0.f : mn;
            const float corr = exp2f(m - mref);
            m = mn;
            l *= corr;
            o[0] *= corr; o[1] *= corr; o[2] *= corr; o[3] *= corr;
#pragma unroll
            for (int u = 0; u < 4; u++) {
                const float pw = exp2f(s[u] - mref);
                l += pw;
                o[0] += pw * __uint_as_float(vv[u].x << 16);
                o[1] += pw * __uint_as_float(vv[u].x & 0xffff0000u);
                o[2] += pw * __uint_as_float(vv[u].y << 16);
                o[3] += pw * __uint_as_float(vv[u].y & 0xffff0000u);
            }
        }
        const float inv = 1.f / l;
#pragma unroll
        for (int u = 0; u < 4; u++) {
            const int d = 4 * lane + u;
            unsigned short* a = reinterpret_cast<unsigned short*>(
                os + (d >> 5) * 10240 + (qn >> 5) * 2048 + (d & 31) * 64 + ((((qn & 31) >> 3) ^ ((d & 7) >> 1)) << 4) + (qn & 7) * 2);
            *a = (unsigned short)(pack_bf16(o[u] * inv, 0.f) & 0xffffu);
        }
    }
}

#define CTA_COORDS()                                   \
    int cta;                                           \
    asm volatile("mov.u32 %0, %ctaid.x;" : "=r"(cta)); \
    const int g = cta >> 3, j = cta & 7, br = cta >> 6, b = g & 7; \
    (void)g; (void)j; (void)br; (void)b

__global__ void __launch_bounds__(512, 1) mha_fused_kernel(const __grid_constant__ Params prm) {
    extern __shared__ __align__(1024) unsigned char smem_raw[];
    if ((uint32_t)__cvta_generic_to_shared(smem_raw) != sb) __trap();
    const int wg = __shfl_sync(0xffffffffu, threadIdx.x >> 7, 0);
    const int lane = threadIdx.x & 31;

    if ((threadIdx.x >> 5) == 2) {
        if (elect_one()) {
            CTA_COORDS();
#pragma unroll
            for (int i = 0; i < 12; i++) mbar_init(sb + B_PRFULL + 8 * i, 1);
            asm volatile("fence.mbarrier_init.release.cluster;" ::: "memory");
            asm volatile("fence.proxy.async.shared::cta;" ::: "memory");
#pragma unroll 1
            for (int n = 0; n < NPRE; n++) {
                const uint32_t s = (8 - (n & 12)) + (n & 3);
                mbar_expect(sb + B_PRFULL + 8 * s, PR_BYTES);
                tma3(sb + s * PR_BYTES, &prm.wq[br], 0, n * 32, 2 * j, sb + B_PRFULL + 8 * s);
                tma2(sb + s * PR_BYTES + 8192, &prm.x[br], n * 32, b * SQ, sb + B_PRFULL + 8 * s);
            }
        }
        __syncwarp();
    } else if (threadIdx.x >= 128 && lane < 8) {
        const uint32_t a = SM_BAR + 8 * ((threadIdx.x >> 5) - 4 + 12 * lane);
        const bool one = a < B_KEMPTY || (a >= B_VFULL && a < B_VEMPTY) || (a >= B_QFULL && a < B_QREADY) ||
                         (a >= B_QVIS && a < B_PREMPTY) || (a >= B_ORDY && a < B_KVGO);
        if (a < B_PRFULL || a >= B_PREMPTY) mbar_init(sb + a, one ? 1 : 4);
        asm volatile("fence.mbarrier_init.release.cluster;" ::: "memory");
        asm volatile("fence.proxy.async.shared::cta;" ::: "memory");
    }
    __syncthreads();

    if (wg == 0) {
        asm volatile("setmaxnreg.dec.sync.aligned.u32 24;");
        const int warp = __shfl_sync(0xffffffffu, warp_now(), 0);
        if (warp == 0) {
            if (elect_one()) {
                CTA_COORDS();
                const int row0 = (b * NH + j) * SK;
                mbar_wait(sb + B_KVGO, 0);
#pragma unroll 1
                for (int t = 0; t < 65; t++) {
                    if (t < 64) {
                        const uint32_t s = t & 1;
                        const bool newq = (t & 15) == 1 && t > 1;
                        const unsigned char* qsrc = g_scr + (size_t)(g * 32 + ((t >> 4) - 1) * 8 + j) * 40960;
                        if (newq) {
                            mbar_wait(sb + B_QVIS + 8 * (t >> 4), 0);
                            mbar_wait(sb + B_QFREE, ((t >> 4) & 1) ^ 1);
                            mbar_expect(sb + B_QFULL, 20480);
                            bulk_g2s(sb + SM_Q, qsrc, 20480, sb + B_QFULL);
                        }
                        mbar_wait(sb + B_KEMPTY + 8 * s, ((t >> 1) & 1) ^ 1);
                        if (newq) {
                            mbar_expect(sb + B_QFULL + 8, 20480);
                            bulk_g2s(sb + SM_Q + 20480, qsrc + 20480, 20480, sb + B_QFULL + 8);
                        }
                        mbar_expect(sb + B_KFULL + 8 * s, 16384);
                        tma3_hint(sb + SM_K + s * 16384, &prm.k[br], 0, row0 + (t >> 4) * (8 * SK) + (t & 15) * 64, 0,
                                  sb + B_KFULL + 8 * s, POL_EF);
                    }
#pragma unroll 1
                    for (int u = t == 2 ? 2 : t - 1; u >= 0 && u < (t == 1 ? 2 : t); u++) {
                        const uint32_t s = u & 1;
                        mbar_wait(sb + B_VEMPTY + 8 * s, ((u >> 1) & 1) ^ 1);
                        mbar_expect(sb + B_VFULL + 8 * s, 16384);
                        tma3_hint(sb + SM_V + s * 16384, &prm.v[br], 0, row0 + (u >> 4) * (8 * SK) + (u & 15) * 64, 0,
                                  sb + B_VFULL + 8 * s, POL_EF);
                    }
                }
            }
        } else if (warp == 1) {
            if (lane == 0) {
                CTA_COORDS();
                const unsigned int target = g_epoch[cta] + 1;
#pragma unroll 1
                for (int r = 0; r < 4; r++) {
                    mbar_wait(sb + B_ODONE + 8 * r, 0);
                    asm volatile("st.release.gpu.global.u32 [%0], %1;" ::"l"(g_flag + g * 32 + r * 8 + j), "r"(target) : "memory");
                }
            }
        } else if (warp == 2) {
            if (elect_one()) {
                CTA_COORDS();
                int pf = 8 + (b >> 2);
#pragma unroll 1
                for (int n = NPRE; n < 12; n++) {
                    const uint32_t s = (8 - (n & 12)) + (n & 3);
                    mbar_expect(sb + B_PRFULL + 8 * s, PR_BYTES);
                    tma3(sb + s * PR_BYTES, &prm.wq[br], 0, n * 32, 2 * j, sb + B_PRFULL + 8 * s);
                    tma2(sb + s * PR_BYTES + 8192, &prm.x[br], n * 32, b * SQ, sb + B_PRFULL + 8 * s);
                }
                auto load_q = [&](int q, uint32_t base, uint32_t par) {
                    const uint32_t dst = sb + base * PR_BYTES, bar = sb + B_PRFULL + 8 * base;
                    const int k0 = (q & 7) * 128, hc = 2 * ((q >> 3) * 8 + j);
#pragma unroll
                    for (int i = 0; i < 4; i++) {
                        mbar_wait(bar + (B_PREMPTY - B_PRFULL) + 8 * i, par ^ 1);
                        tma2(dst + i * PR_BYTES + 8192, &prm.x[br], k0 + i * 32, b * SQ, bar + 8 * i);
                        tma3(dst + i * PR_BYTES, &prm.wq[br], 0, k0 + i * 32, hc, bar + 8 * i);
                        mbar_expect(bar + 8 * i, PR_BYTES);
                    }
                    const int mend = q <= 8 ? 8 + HP * (q - 2) : q + PDQ + 1;
                    for (; pf < mend; pf += 2) {
                        if (pf < 32) pf3(&prm.wq[br], 0, (pf & 7) * 128 + (b & 3) * 32, 2 * ((pf >> 3) * 8 + j));
                        else pf3(&prm.wo[br], 0, (pf - 32) * 128 + (b & 3) * 32, 2 * j);
                    }
                };
#pragma unroll 1
                for (int q = 3; q < 8; q++) load_q(q, 4 * (q & 1), ((q - 1) >> 1) & 1);
#pragma unroll 1
                for (int q = 8; q < 32; q++) load_q(q, 0, (q + 1) & 1);
                const unsigned char* osrc = g_scr + (size_t)g * (128 * 10240);
                auto load_o = [&](int q, auto BASE) {
                    constexpr uint32_t dst = sb + BASE.value * PR_BYTES, bar = sb + B_PRFULL + 8 * BASE.value;
                    mbar_wait(sb + B_ORDY + 8 * q, 0);
                    uint32_t hh;
                    asm volatile("ld.shared.u8 %0, [%1];" : "=r"(hh) : "r"(sb + SM_ORD + q) : "memory");
#pragma unroll
                    for (int i = 0; i < 4; i++) {
                        if (BASE.value == 0) mbar_wait(sb + B_PREMPTY + 8 * i, q & 1);
                        tma3(dst + i * PR_BYTES, &prm.wo[br], 0, hh * 128 + i * 32, 2 * j, bar + 8 * i);
                        bulk_g2s(dst + i * PR_BYTES + 8192, osrc + hh * 40960 + i * 10240, 10240, bar + 8 * i);
                        mbar_expect(bar + 8 * i, PR_BYTES);
                    }
                };
#pragma unroll 1
                for (int q = 0; q < 31; q++) {
                    load_o(q, IC<0>{});
                    const int m = q + PDQ;
                    if (m < 24 && (m & 1) == (b >> 2)) pf3(&prm.wo[br], 0, m * 128 + (b & 3) * 32, 2 * j);
                }
                load_o(31, IC<8>{});
            }
        } else {
            CTA_COORDS();
            const unsigned int target = g_epoch[cta] + 1;
            if (lane == 0) {
#pragma unroll 1
                for (int r = 1; r < 4; r++) {
                    mbar_wait(sb + B_QREADY + 8 * r, 0);
                    asm volatile("fence.acq_rel.gpu;" ::: "memory");
                    asm volatile("fence.proxy.async.global;" ::: "memory");
                    mbar_arrive(sb + B_QVIS + 8 * r);
                    if (r == 2) break;
                }
            }
            __syncwarp();
            int nr = 0;
            unsigned int seen = 0;
            bool q3 = false;
            unsigned int it = 0;
            while (nr < 32) {
                if (!q3 && mbar_test(sb + B_QREADY + 24, 0)) {
                    if (lane == 0) {
                        asm volatile("fence.acq_rel.gpu;" ::: "memory");
                        asm volatile("fence.proxy.async.global;" ::: "memory");
                        mbar_arrive(sb + B_QVIS + 24);
                    }
                    q3 = true;
                }
                unsigned int v;
                asm volatile("ld.acquire.gpu.global.u32 %0, [%1];" : "=r"(v) : "l"(g_flag + g * 32 + lane) : "memory");
                unsigned int fresh = __ballot_sync(0xffffffffu, v == target);
                fresh &= ~seen;
                if (fresh) {
                    asm volatile("fence.proxy.async.global;" ::: "memory");
                    if ((fresh >> lane) & 1) {
                        const uint32_t pos = nr + __popc(fresh & ((1u << lane) - 1));
                        asm volatile("st.shared.u8 [%0], %1;" ::"r"(sb + SM_ORD + pos), "r"(lane) : "memory");
                        mbar_arrive(sb + B_ORDY + 8 * pos);
                    }
                    nr += __popc(fresh);
                    seen |= fresh;
                }
                if (nr < 24) __nanosleep(400);
                else if (!mbar_test(sb + B_ADONE, 0)) __nanosleep(150);
                if (++it > 8388608u) __trap();
                __syncwarp();
            }
            if (lane == 0) g_epoch[cta] = target;
        }
    } else if (wg == 1) {
        asm volatile("setmaxnreg.dec.sync.aligned.u32 104;");
        float s[40], x[40];
#pragma unroll
        for (int i = 0; i < 40; i++) s[i] = x[i] = 0.f;
        const uint32_t t8 = lane & 7, m = lane >> 3;
        const uint32_t pst = sb + SM_P + (8 * (m >> 1) + t8) * 128 + (((2 * warp_now() + (m & 1)) ^ t8) << 4);
        auto qk = [&](uint32_t sl, int hf) {
            const uint64_t da = mkdesc<16, 1024, 1>(sb + SM_K + sl * 16384);
            const uint64_t db = mkdesc<4096, 256, 3>(sb + SM_Q + hf * 20480);
            wg_fence();
#pragma unroll
            for (int kk = 0; kk < 8; kk++)
                wgmma80<0, 1>(s, da + (((kk >> 2) * 8192 + (kk & 3) * 32) >> 4), db + ((kk * 512) >> 4), kk != 0 ? 1 : prm.zero);
            wg_commit();
        };
        auto expo = [&](uint32_t pa, int jj) {
            stsm4t(pa + jj * 2048, pack_bf16(ex2(x[8 * jj]), ex2(x[8 * jj + 1])), pack_bf16(ex2(x[8 * jj + 2]), ex2(x[8 * jj + 3])),
                   pack_bf16(ex2(x[8 * jj + 4]), ex2(x[8 * jj + 5])), pack_bf16(ex2(x[8 * jj + 6]), ex2(x[8 * jj + 7])));
        };
        auto stage = [&]() {
            wg_wait<0>();
            acc_fence(s);
#pragma unroll
            for (int i = 0; i < 40; i++) x[i] = s[i] * QSCALE;
            acc_fence(x);
        };
        mbar_wait(sb + B_QREADY, 0);
        mbar_wait(sb + B_KFULL, 0);
        qk(0, 0);
#pragma unroll 1
        for (int t2 = 0; t2 < 32; t2++) {
            const uint32_t ph = t2 & 1;
            static_for<2>([&](auto SL) {
                constexpr uint32_t sl = SL.value;
                const uint32_t pa = pst + sl * P_BYTES;
                stage();
                mbar_wait(sb + B_PEMPTY + 8 * sl, ph ^ 1);
                if (sl == 0 && (t2 & 7) == 0 && t2 != 0) mbar_wait(sb + B_QFULL + 8, ((t2 >> 3) & 1) ^ 1);
                qk(sl, 1);
                SCHED_FENCE(t2, sl);
                expo(pa, 0);
                expo(pa, 1);
                expo(pa, 2);
                expo(pa, 3);
                wg_wait<0>();
                mbar_arrive_warp(sb + B_KEMPTY + 8 * sl);
                expo(pa, 4);
                stage();
                const bool last = sl == 1 && (t2 & 7) == 7;
                if (!last) {
                    mbar_wait(sb + B_KFULL + 8 * (sl ^ 1), sl == 0 ? ph : ph ^ 1);
                    qk(sl ^ 1, 0);
                    if (sl == 0) SCHED_FENCE(t2, 2);
                }
                expo(pa + 10240, 0);
                expo(pa + 10240, 1);
                expo(pa + 10240, 2);
                if (sl == 0 && (t2 & 7) == 7) {
                    wg_wait<0>();
                    mbar_arrive_warp(sb + B_QFREE);
                }
                expo(pa + 10240, 3);
                expo(pa + 10240, 4);
                asm volatile("fence.acq_rel.cta;" ::: "memory");
                __syncwarp();
                mbar_arrive_warp(sb + B_PFULL + 8 * sl);
                if (last && t2 != 31) {
                    mbar_wait(sb + B_QFULL, (t2 >> 3) & 1);
                    mbar_wait(sb + B_KFULL, ph ^ 1);
                    qk(0, 0);
                }
            });
        }
        wg_wait<0>();
    } else if (wg == 2) {
        asm volatile("setmaxnreg.inc.sync.aligned.u32 192;");
        float o0[80], o1[80];
        const uint32_t prow = warp_now() * 8 + (lane >> 2);
        const uint32_t pld = prow * 128 + (((lane & 3) | ((prow & 1) << 2)) << 4);
#pragma unroll 1
        for (int r = 0; r < 4; r++) {
            float l[5] = {0.f, 0.f, 0.f, 0.f, 0.f};
            bool bad = false;
            auto pv_begin = [&](auto SL, auto ACC, uint32_t ph) {
                constexpr uint32_t sl = SL.value;
                mbar_wait(sb + B_VFULL + 8 * sl, ph);
                mbar_wait(sb + B_PFULL + 8 * sl, ph);
                asm volatile("fence.proxy.async.shared::cta;" ::: "memory");
                wg_fence();
                wgmma160<1, 0>(o0, mkdesc<16, 1024, 1>(sb + SM_V + sl * 16384), mkdesc<16, 1024, 1>(sb + SM_P + sl * P_BYTES), ACC.value);
                wg_commit();
                wgmma160<1, 0>(o1, mkdesc<16, 1024, 1>(sb + SM_V + sl * 16384 + 8192), mkdesc<16, 1024, 1>(sb + SM_P + sl * P_BYTES), ACC.value);
                wg_commit();
            };
            pv_begin(IC<0>{}, IC<0>{}, 0);
#pragma unroll 1
            for (int i2 = 0; i2 < 8; i2++) static_for<2>([&](auto SL) {
                constexpr uint32_t sl = SL.value;
                const uint64_t da = mkdesc<16, 1024, 1>(sb + SM_V + sl * 16384);
                const uint64_t db = mkdesc<16, 1024, 1>(sb + SM_P + sl * P_BYTES);
                if (sl == 0) wg_fence();
                uint32_t w[8];
                static_for<8, 2>([&](auto K) {
                    constexpr int k = K.value;
                    if constexpr (k >= PVW) wg_wait<PVW - 1>();
                    if constexpr (k >= 4) wg_fence();
                    if (k & 1) wgmma160<1, 0>(o1, da + ((8192 + (k >> 1) * 2048) >> 4), db + (((k >> 1) * 32) >> 4), 1);
                    else wgmma160<1, 0>(o0, da + (((k >> 1) * 2048) >> 4), db + (((k >> 1) * 32) >> 4), 1);
                    wg_commit();
                    if constexpr (k >= 4) lsum(l[k - 4], w);
                    if constexpr (k >= 3) {
                        lds128u<sb + SM_P + sl * P_BYTES + (k - 3) * 4096>(pld, w);
                        lds128u<sb + SM_P + sl * P_BYTES + (k - 3) * 4096>(pld ^ 64, w + 4);
                        SCHED_FENCE(i2, k + 8 * sl);
                    }
                });
                lsum(l[4], w);
                if (sl == 1 && i2 == 7) {
#pragma unroll
                    for (int k = 0; k < 5; k++) l[k] += __shfl_xor_sync(0xffffffffu, l[k], 1);
#pragma unroll
                    for (int k = 0; k < 5; k++) l[k] += __shfl_xor_sync(0xffffffffu, l[k], 2);
                    const uint32_t ln = lane_now();
                    const uint32_t la = sb + SM_LINV + (((ln >> 3) & 3) * 8 + warp_now() * 2 + ((ln >> 2) & 1)) * 4;
#pragma unroll
                    for (int k = 0; k < 5; k++) {
                        bad |= !(l[k] >= 0.00390625f && l[k] <= 4294967296.f);
                        float v;
                        asm("rcp.approx.ftz.f32 %0, %1;" : "=f"(v) : "f"(l[k]));
                        if ((ln & 3) == 0) asm volatile("st.shared.f32 [%0], %1;" ::"r"(la + 128 * k), "f"(v) : "memory");
                    }
                }
                wg_wait<0>();
                __syncwarp();
                mbar_arrive_warp(sb + B_PEMPTY + 8 * sl);
                mbar_arrive_warp(sb + B_VEMPTY + 8 * sl);
                if (sl == 0) pv_begin(IC<1>{}, IC<1>{}, i2 & 1);
                else if (i2 != 7) pv_begin(IC<0>{}, IC<1>{}, (i2 & 1) ^ 1);
            });
            wg_wait<0>();
            if (r == 3) mbar_arrive_warp(sb + B_ADONE);
            acc_fence(o0);
            acc_fence(o1);
            uint32_t redo;
            asm volatile("{\n.reg .pred p, q;\nsetp.ne.u32 p, %1, 0;\nbar.red.or.pred q, 1, 128, p;\nselp.u32 %0, 1, 0, q;\n}"
                         : "=r"(redo) : "r"((uint32_t)bad) : "memory");
            if (r < 3) mbar_wait(sb + B_QFULL, r & 1);
            CTA_COORDS();
            unsigned char* os = g_scr + (size_t)(g * 32 + 8 * r + j) * 40960;
            if (__any_sync(0xffffffffu, redo)) {
                const int h = 8 * r + j;
                if (r < 3) mbar_wait(sb + B_QFULL + 8, r & 1);
                slow_head(prm.xp[br] + (size_t)b * SQ * 1024, prm.wqp[br] + h * 128, prm.kp[br] + (size_t)(b * NH + h) * SK * 128,
                          prm.vp[br] + (size_t)(b * NH + h) * SK * 128, os, warp_now(), lane_now());
            } else {
                const uint32_t ln = lane_now(), g8 = ln >> 2, warp = warp_now();
                unsigned char* op = os + (warp >> 1) * 10240 + (16 * (warp & 1) + g8) * 64 + (((ln & 3) ^ (g8 >> 1)) << 4);
                const uint32_t li = (ln & 3) * 32;
                float iv[40];
                lds128i<sb + SM_LINV>(li, iv);
                lds128i<sb + SM_LINV + 16>(li, iv + 4);
                auto put = [&](const float* o, const float* v, unsigned char* p) {
                    stg128(p, pack_bf16(o[0] * v[0], o[1] * v[1]), pack_bf16(o[4] * v[2], o[5] * v[3]),
                           pack_bf16(o[8] * v[4], o[9] * v[5]), pack_bf16(o[12] * v[6], o[13] * v[7]));
                };
                static_for<5>([&](auto I) {
                    constexpr int i = I.value;
                    if constexpr (i < 4) {
                        lds128i<sb + SM_LINV + 128 * (i + 1)>(li, iv + 8 * (i + 1));
                        lds128i<sb + SM_LINV + 128 * (i + 1) + 16>(li, iv + 8 * (i + 1) + 4);
                    }
                    put(o0 + 16 * i, iv + 8 * i, op + i * 2048);
                    put(o0 + 16 * i + 2, iv + 8 * i, op + i * 2048 + 512);
                });
                if (r < 3) mbar_wait(sb + B_QFULL + 8, r & 1);
                static_for<5>([&](auto I) {
                    constexpr int i = I.value;
                    put(o1 + 16 * i, iv + 8 * i, op + 20480 + i * 2048);
                    put(o1 + 16 * i + 2, iv + 8 * i, op + 20480 + i * 2048 + 512);
                });
            }
            __syncwarp();
            mbar_arrive_warp(sb + B_ODONE + 8 * r);
        }
    } else {
        asm volatile("setmaxnreg.inc.sync.aligned.u32 192;");
        float a0[80], a1[80];
        const bool leader = lane == 0;
        {
            uint32_t pbase = 0;
#pragma unroll 1
            for (int q = 0; q < 8; q++) {
                const uint32_t base = q == 0 ? 8 : 4 * (q & 1), par = q == 0 ? 0 : ((q - 1) >> 1) & 1;
                if (leader && q == KV_START) mbar_arrive(sb + B_KVGO);
                quad_alone(a0, a1, base, par, pbase, q, leader);
                pbase = base;
            }
            const uint32_t ln = lane_now(), g8 = ln >> 2;
            const uint32_t qo = ((ln >> 1) & 1) * 4096 + (16 * warp_now() + g8) * 32 + (((ln & 1) ^ (g8 >> 2)) << 4);
            wg_wait<0>();
            acc_fence(a0);
            acc_fence(a1);
            asm volatile("bar.sync 2, 128;" ::: "memory");
            static_for<20>([&](auto I) {
                constexpr int i = I.value, a = 16 * (i >> 2) + 2 * (i & 1);
                const float* v = (i & 2) ? a1 : a0;
                sts128i<sb + SM_Q + (i >> 2) * 8192 + ((i >> 1) & 1) * 2048 + (i & 1) * 256>(
                    qo, pack_bf16(v[a], v[a + 1]), pack_bf16(v[a + 4], v[a + 5]), pack_bf16(v[a + 8], v[a + 9]),
                    pack_bf16(v[a + 12], v[a + 13]));
            });
            asm volatile("fence.proxy.async.shared::cta;" ::: "memory");
            __syncwarp();
            mbar_arrive_warp(sb + B_QREADY);
        }
#pragma unroll 1
        for (int r = 1; r < 4; r++) {
            quad_shared<PWQ, 0, 0>(a0, a1, 1, leader);
#pragma unroll 1
            for (int q = 1; q < 8; q++) {
                quad_shared<PWQ, 0>(a0, a1, (q + 1) & 1, leader);
            }
            CTA_COORDS();
            const uint32_t ln = lane_now(), g8 = ln >> 2;
            unsigned char* qp = g_scr + (size_t)(g * 32 + (r - 1) * 8 + j) * 40960 + ((ln >> 1) & 1) * 4096 +
                                (16 * warp_now() + g8) * 32 + (((ln & 1) ^ (g8 >> 2)) << 4);
            wg_wait<0>();
            acc_fence(a0);
            acc_fence(a1);
            mbar_arrive_warp(sb + B_PREMPTY + 8 * 3);
#pragma unroll
            for (int i = 0; i < 20; i++) {
                const int a = 16 * (i >> 2) + 2 * (i & 1);
                const float* v = (i & 2) ? a1 : a0;
                stg128(qp + (i >> 2) * 8192 + ((i >> 1) & 1) * 2048 + (i & 1) * 256, pack_bf16(v[a], v[a + 1]),
                       pack_bf16(v[a + 4], v[a + 5]), pack_bf16(v[a + 8], v[a + 9]), pack_bf16(v[a + 12], v[a + 13]));
            }
            __syncwarp();
            mbar_arrive_warp(sb + B_QREADY + 8 * r);
        }
        bool alone = false;
        quad_shared<PWO, 1, 0>(a0, a1, 1, leader);
#pragma unroll 1
        for (int q = 33; q < 63; q++) {
            const bool rel0 = q < 48 || mbar_test(sb + B_ORDY + 8 * (q - 32), 0);
            if (!rel0) {
                wg_wait<0>();
                if (leader) mbar_arrive(sb + B_PREMPTY + 8 * 3);
            }
            if (!alone && q >= 48) {
                mbar_wait(sb + B_PRFULL, (q + 1) & 1);
                uint32_t a;
                asm volatile("{\n.reg .pred p, q;\nmbarrier.test_wait.parity.shared::cta.b64 p, [%1], 0;\n"
                             "bar.red.and.pred q, 2, 128, p;\nselp.u32 %0, 1, 0, q;\n}" : "=r"(a) : "r"(sb + B_ADONE) : "memory");
                alone = a != 0;
            }
            if (alone) quad_shared<PWT, 1>(a0, a1, (q + 1) & 1, leader, rel0);
            else quad_shared<PWO, 1>(a0, a1, (q + 1) & 1, leader, rel0);
        }
        const uint32_t ln = lane_now(), t8 = ln & 7, m = ln >> 3, warp = __shfl_sync(0xffffffffu, warp_now(), 0);
        const uint32_t pst = sb + SM_Q + (8 * (m >> 1) + t8) * 128 + (((2 * warp + (m & 1)) ^ t8) << 4);
        static_for<4>([&](auto I) {
            constexpr uint32_t a = sb + (8 + I.value) * PR_BYTES;
            mbar_wait(sb + B_PRFULL + 8 * (8 + I.value), 1);
            wg_fence();
            wgmma160<1, 1>(a0, mkdesc<16, 1024, 1>(a), mkdesc<2048, 512, 2>(a + 8192), 1);
            wgmma160<1, 1>(a0, mkdesc<16, 1024, 1>(a + 2048), mkdesc<2048, 512, 2>(a + 9216), 1);
            wg_commit();
        });
        static_for<4>([&](auto I) {
            constexpr uint32_t a = sb + (8 + I.value) * PR_BYTES;
            wgmma160<1, 1>(a1, mkdesc<16, 1024, 1>(a + 4096), mkdesc<2048, 512, 2>(a + 8192), 1);
            wgmma160<1, 1>(a1, mkdesc<16, 1024, 1>(a + 6144), mkdesc<2048, 512, 2>(a + 9216), 1);
        });
        wg_commit();
        auto put_half = [&](const float (&a)[80], auto H) {
            static_for<OCH>([&](auto C) {
                constexpr int c = C.value, per = 10 / OCH;
#pragma unroll
                for (int jj = c * per; jj < (c + 1) * per; jj++)
                    stsm4t(pst + H.value * P_BYTES + jj * 2048, pack_bf16(a[8 * jj], a[8 * jj + 1]), pack_bf16(a[8 * jj + 2], a[8 * jj + 3]),
                           pack_bf16(a[8 * jj + 4], a[8 * jj + 5]), pack_bf16(a[8 * jj + 6], a[8 * jj + 7]));
                asm volatile("fence.proxy.async.shared::cta;" ::: "memory");
                if (warp == (c & 3)) {
                    asm volatile("bar.sync %0, 128;" ::"n"(3 + (H.value * OCH + c) % 10) : "memory");
                    if (elect_one()) {
                        CTA_COORDS();
                        tma2_store(&prm.out, sb + SM_Q + H.value * P_BYTES + c * per * 2048, br * 1024 + j * 128 + H.value * 64,
                                   b * SQ + c * per * 16);
                        asm volatile("cp.async.bulk.commit_group;" ::: "memory");
                    }
                    __syncwarp();
                } else {
                    asm volatile("bar.arrive %0, 128;" ::"n"(3 + (H.value * OCH + c) % 10) : "memory");
                }
            });
        };
        wg_wait<1>();
        acc_fence(a0);
        put_half(a0, IC<0>{});
        wg_wait<0>();
        acc_fence(a1);
        put_half(a1, IC<1>{});
        asm volatile("cp.async.bulk.wait_group 0;" ::: "memory");
    }
}

typedef CUresult (*EncodeFn)(CUtensorMap*, CUtensorMapDataType, cuuint32_t, void*, const cuuint64_t*, const cuuint64_t*,
                             const cuuint32_t*, const cuuint32_t*, CUtensorMapInterleave, CUtensorMapSwizzle,
                             CUtensorMapL2promotion, CUtensorMapFloatOOBfill);

void encode(EncodeFn fn, CUtensorMap* m, void* p, int rank, const cuuint64_t* dims, const cuuint64_t* strides,
            const cuuint32_t* box, CUtensorMapSwizzle swz) {
    cuuint32_t es[3] = {1, 1, 1};
    fn(m, CU_TENSOR_MAP_DATA_TYPE_BFLOAT16, rank, p, dims, strides, box, es, CU_TENSOR_MAP_INTERLEAVE_NONE, swz,
       CU_TENSOR_MAP_L2_PROMOTION_L2_128B, CU_TENSOR_MAP_FLOAT_OOB_FILL_NONE);
}

}


extern "C" void kernel_launch(void* const* d_in, const int* in_sizes, int n_in, void* d_out, int out_size) {
    static EncodeFn fn = nullptr;
    if (!fn) {
        void* f = nullptr;
        cudaDriverEntryPointQueryResult st;
        cudaGetDriverEntryPoint("cuTensorMapEncodeTiled", &f, cudaEnableDefault, &st);
        fn = (EncodeFn)f;
        cudaFuncSetAttribute(mha_fused_kernel, cudaFuncAttributeMaxDynamicSharedMemorySize, SM_TOTAL);
    }
    Params prm;
    prm.zero = 0;
    prm.never = 1 << 20;
    for (int br = 0; br < 2; br++) {
        void* x = d_in[5 * br + 0];
        void* k = d_in[5 * br + 1];
        void* v = d_in[5 * br + 2];
        void* wq = d_in[5 * br + 3];
        void* wo = d_in[5 * br + 4];
        {
            cuuint64_t dims[3] = {64, 8ull * NH * SK, 2}, str[2] = {256, 128};
            cuuint32_t box[3] = {64, 64, 2};
            encode(fn, &prm.k[br], k, 3, dims, str, box, CU_TENSOR_MAP_SWIZZLE_128B);
            encode(fn, &prm.v[br], v, 3, dims, str, box, CU_TENSOR_MAP_SWIZZLE_128B);
        }
        {
            cuuint64_t dims[3] = {64, 1024, 64}, str[2] = {8192, 128};
            cuuint32_t box[3] = {64, 32, 2};
            encode(fn, &prm.wq[br], wq, 3, dims, str, box, CU_TENSOR_MAP_SWIZZLE_128B);
        }
        {
            cuuint64_t dims[3] = {64, 4096, 16}, str[2] = {2048, 128};
            cuuint32_t box[3] = {64, 32, 2};
            encode(fn, &prm.wo[br], wo, 3, dims, str, box, CU_TENSOR_MAP_SWIZZLE_128B);
        }
        {
            cuuint64_t dims[2] = {1024, 1280}, str[1] = {2048};
            cuuint32_t box[2] = {32, 160};
            encode(fn, &prm.x[br], x, 2, dims, str, box, CU_TENSOR_MAP_SWIZZLE_64B);
        }
        prm.kp[br] = (const __nv_bfloat16*)k;
        prm.vp[br] = (const __nv_bfloat16*)v;
        prm.xp[br] = (const __nv_bfloat16*)x;
        prm.wqp[br] = (const __nv_bfloat16*)wq;
    }
    {
        cuuint64_t dims[2] = {2048, 1280}, str[1] = {4096};
        cuuint32_t box[2] = {64, 160 / OCH};
        encode(fn, &prm.out, d_out, 2, dims, str, box, CU_TENSOR_MAP_SWIZZLE_128B);
    }
    mha_fused_kernel<<<NCTA, 512, SM_TOTAL, cudaStreamPerThread>>>(prm);
}
```

```cpp
#include <cuda_runtime.h>
#include <cuda_bf16.h>
#include <cuda.h>
#include <stdint.h>

namespace {

constexpr int SQ = 160, SK = 1024, NH = 32;
constexpr int NCTA = 128;

constexpr uint32_t sb = 1024;
constexpr uint32_t PR_BYTES = 18432;
constexpr uint32_t SM_Q = 4 * PR_BYTES;
constexpr uint32_t SM_P = SM_Q + 40960;
constexpr uint32_t P_BYTES = 20480;
constexpr uint32_t SM_K = SM_P + 2 * P_BYTES;
constexpr uint32_t SM_V = SM_K + 2 * 16384;
constexpr uint32_t SM_LINV = SM_V + 2 * 16384;
constexpr uint32_t SM_BAR = SM_LINV + 160 * 4;
constexpr uint32_t SM_ORD = SM_BAR + 768;
constexpr uint32_t SM_TOTAL = SM_ORD + 32;
static_assert(SM_V + 2 * 16384 == 12 * PR_BYTES, "Q/P/K/V double as stage slots 4..11 before and after attention");
constexpr uint32_t B_KFULL = SM_BAR + 0;
constexpr uint32_t B_KEMPTY = SM_BAR + 16;
constexpr uint32_t B_VFULL = SM_BAR + 32;
constexpr uint32_t B_VEMPTY = SM_BAR + 48;
constexpr uint32_t B_PFULL = SM_BAR + 64;
constexpr uint32_t B_PEMPTY = SM_BAR + 80;
constexpr uint32_t B_QFULL = SM_BAR + 96;
constexpr uint32_t B_QREADY = SM_BAR + 112;
constexpr uint32_t B_ODONE = SM_BAR + 144;
constexpr uint32_t B_QVIS = SM_BAR + 176;
constexpr uint32_t B_PRFULL = SM_BAR + 208;
constexpr uint32_t B_PREMPTY = SM_BAR + 304;
constexpr uint32_t B_ORDY = SM_BAR + 400;
constexpr uint32_t B_KVGO = SM_BAR + 656;
constexpr uint32_t B_QFREE = SM_BAR + 672;
constexpr uint32_t B_ADONE = SM_BAR + 680;
constexpr uint32_t B_END = SM_BAR + 688;
constexpr int KV_START = 7;
constexpr int NPRE = 4;
constexpr int PDQ = 5;
constexpr int HP = 2;
constexpr int OCH = 2;
constexpr int DIRA = 8, DIRB = 20;
constexpr int PVW = 3;
constexpr int PWQ = 1212, PWO = 2, PWT = 4;

template <int V> struct IC { static constexpr int value = V; };
template <int N, int I = 0, class F> __device__ __forceinline__ void static_for(F&& f) {
    if constexpr (I < N) {
        f(IC<I>{});
        static_for<N, I + 1>(f);
    }
}

struct Params {
    CUtensorMap k[2], v[2], x[2], wq[2], wo[2], out;
    const __nv_bfloat16* kp[2];
    const __nv_bfloat16* vp[2];
    const __nv_bfloat16* xp[2];
    const __nv_bfloat16* wqp[2];
    int zero;
    float one;
    int never;
};

__device__ __align__(1024) unsigned char g_scr[16 * 32 * 40960];
__device__ __align__(128) unsigned int g_flag[16 * 32];
__device__ unsigned int g_epoch[NCTA];

__device__ __forceinline__ void mbar_init(uint32_t b, int c) {
    asm volatile("mbarrier.init.shared::cta.b64 [%0], %1;" ::"r"(b), "r"(c));
}
__device__ __forceinline__ void mbar_expect(uint32_t b, int bytes) {
    asm volatile("mbarrier.arrive.expect_tx.shared::cta.b64 _, [%0], %1;" ::"r"(b), "r"(bytes) : "memory");
}
__device__ __forceinline__ void mbar_arrive(uint32_t b) {
    asm volatile("mbarrier.arrive.shared::cta.b64 _, [%0];" ::"r"(b) : "memory");
}
__device__ __forceinline__ void mbar_arrive_warp(uint32_t b) {
    asm volatile("{\n.reg .pred p;\nelect.sync _|p, 0xffffffff;\n@p mbarrier.arrive.shared::cta.b64 _, [%0];\n}" ::"r"(b) : "memory");
}
__device__ __forceinline__ bool elect_one() {
    uint32_t r;
    asm volatile("{\n.reg .pred p;\nelect.sync _|p, 0xffffffff;\nselp.u32 %0, 1, 0, p;\n}" : "=r"(r));
    return r != 0;
}
__device__ __forceinline__ uint32_t warp_now() {
    uint32_t r;
    asm volatile("mov.u32 %0, %tid.x;" : "=r"(r));
    return (r >> 5) & 3;
}
__device__ __forceinline__ uint32_t lane_now() {
    uint32_t r;
    asm volatile("mov.u32 %0, %laneid;" : "=r"(r));
    return r;
}
__device__ __forceinline__ void mbar_wait(uint32_t b, uint32_t ph) {
    asm volatile("{\n.reg .pred p;\nW:\nmbarrier.try_wait.parity.shared::cta.b64 p, [%0], %1;\n@!p bra W;\n}" ::"r"(b), "r"(ph) : "memory");
}
__device__ __forceinline__ void mbar_wait_lim(uint32_t b, uint32_t ph) {
    asm volatile(
        "{\n.reg .pred p;\n.reg .u32 n;\n"
        "mbarrier.try_wait.parity.shared::cta.b64 p, [%0], %1;\n"
        "@p bra D;\n"
        "mov.u32 n, 0;\n"
        "W:\nmbarrier.try_wait.parity.shared::cta.b64 p, [%0], %1;\n"
        "@p bra D;\n"
        "add.u32 n, n, 1;\nsetp.lt.u32 p, n, 4194304;\n@p bra W;\ntrap;\n"
        "D:\n}" ::"r"(b), "r"(ph) : "memory");
}
__device__ __forceinline__ bool mbar_test(uint32_t b, uint32_t ph) {
    uint32_t r;
    asm volatile("{\n.reg .pred p;\nmbarrier.test_wait.parity.shared::cta.b64 p, [%1], %2;\nselp.u32 %0, 1, 0, p;\n}"
                 : "=r"(r) : "r"(b), "r"(ph) : "memory");
    return r != 0;
}
__device__ __forceinline__ void pfw(const CUtensorMap* m, int row, int cb) {
    asm volatile("cp.async.bulk.prefetch.tensor.4d.L2.global [%0, {%1, %1, %2, %3}];" ::"l"(m), "r"(0), "r"(cb), "r"(row >> 3) : "memory");
}
constexpr uint64_t POL_EF = 0x12F0000000000000ull;
__device__ __forceinline__ void tmaw(uint32_t dst, const CUtensorMap* m, int row, int cb, uint32_t bar) {
    asm volatile("cp.async.bulk.tensor.4d.shared::cluster.global.mbarrier::complete_tx::bytes [%0], [%1, {%3, %3, %4, %5}], [%2];"
                 ::"r"(dst), "l"(m), "r"(bar), "r"(0), "r"(cb), "r"(row >> 3) : "memory");
}
__device__ __forceinline__ void tma4_hint(uint32_t dst, const CUtensorMap* m, int c3, uint32_t bar, uint64_t pol) {
    asm volatile("cp.async.bulk.tensor.4d.shared::cluster.global.mbarrier::complete_tx::bytes.L2::cache_hint [%0], [%1, {%3, %3, %3, %4}], [%2], %5;"
                 ::"r"(dst), "l"(m), "r"(bar), "r"(0), "r"(c3), "l"(pol) : "memory");
}
__device__ __forceinline__ void tma2(uint32_t dst, const CUtensorMap* m, int c0, int c1, uint32_t bar) {
    asm volatile("cp.async.bulk.tensor.2d.shared::cluster.global.mbarrier::complete_tx::bytes [%0], [%1, {%3, %4}], [%2];"
                 ::"r"(dst), "l"(m), "r"(bar), "r"(c0), "r"(c1) : "memory");
}
__device__ __forceinline__ void bulk_g2s(uint32_t dst, const void* src, int bytes, uint32_t bar) {
    asm volatile("cp.async.bulk.shared::cluster.global.mbarrier::complete_tx::bytes [%0], [%1], %2, [%3];"
                 ::"r"(dst), "l"(src), "r"(bytes), "r"(bar) : "memory");
}
__device__ __forceinline__ void tma2_store(const CUtensorMap* m, uint32_t src, int c0, int c1) {
    asm volatile("cp.async.bulk.tensor.2d.global.shared::cta.bulk_group [%0, {%2, %3}], [%1];"
                 ::"l"(m), "r"(src), "r"(c0), "r"(c1) : "memory");
}
__device__ __forceinline__ void wg_fence() { asm volatile("wgmma.fence.sync.aligned;" ::: "memory"); }
__device__ __forceinline__ void wg_commit() { asm volatile("wgmma.commit_group.sync.aligned;" ::: "memory"); }
template <int N> __device__ __forceinline__ void wg_wait() { asm volatile("wgmma.wait_group.sync.aligned %0;" ::"n"(N) : "memory"); }
template <int N> __device__ __forceinline__ void acc_fence(float (&d)[N]) {
#pragma unroll
    for (int i = 0; i < N; i++) asm volatile("" : "+f"(d[i])::"memory");
}
template <uint32_t OFF> __device__ __forceinline__ void sts128i(uint32_t p, uint32_t a, uint32_t b, uint32_t c, uint32_t d) {
    asm volatile("st.shared.v4.u32 [%0+%5], {%1, %2, %3, %4};" ::"r"(p), "r"(a), "r"(b), "r"(c), "r"(d), "n"(OFF) : "memory");
}
template <uint32_t OFF> __device__ __forceinline__ void lds128i(uint32_t p, float* v) {
    asm volatile("ld.shared.v4.f32 {%0, %1, %2, %3}, [%4+%5];" : "=f"(v[0]), "=f"(v[1]), "=f"(v[2]), "=f"(v[3]) : "r"(p), "n"(OFF) : "memory");
}
template <uint32_t OFF> __device__ __forceinline__ void lds128u(uint32_t p, uint32_t* v) {
    asm volatile("ld.shared.v4.u32 {%0, %1, %2, %3}, [%4+%5];" : "=r"(v[0]), "=r"(v[1]), "=r"(v[2]), "=r"(v[3]) : "r"(p), "n"(OFF) : "memory");
}
#define SCHED_FENCE(cnt, k) do { if ((cnt) == prm.never + (int)(k)) { wg_wait<0>(); __trap(); } } while (0)
template <uint32_t LBO, uint32_t SBO, uint32_t SWZ>
__device__ __forceinline__ uint64_t mkdesc(uint32_t addr) {
    uint32_t lo = ((addr & 0x3FFFF) >> 4) | ((LBO >> 4) << 16);
    uint32_t hi = (SBO >> 4) | (SWZ << 30);
    return ((uint64_t)hi << 32) | lo;
}

template <int TA, int TB>
__device__ __forceinline__ void wgmma160(float (&d)[80], uint64_t da, uint64_t db, int scale_d) {
    asm volatile(
        "{\n.reg .pred p;\nsetp.ne.b32 p, %82, 0;\n"
        "wgmma.mma_async.sync.aligned.m64n160k16.f32.bf16.bf16 "
        "{%0, %1, %2, %3, %4, %5, %6, %7, %8, %9, %10, %11, %12, %13, %14, %15, %16, %17, %18, %19, "
        "%20, %21, %22, %23, %24, %25, %26, %27, %28, %29, %30, %31, %32, %33, %34, %35, %36, %37, %38, %39, "
        "%40, %41, %42, %43, %44, %45, %46, %47, %48, %49, %50, %51, %52, %53, %54, %55, %56, %57, %58, %59, "
        "%60, %61, %62, %63, %64, %65, %66, %67, %68, %69, %70, %71, %72, %73, %74, %75, %76, %77, %78, %79}, "
        "%80, %81, p, 1, 1, %83, %84;\n}\n"
        : "+f"(d[0]), "+f"(d[1]), "+f"(d[2]), "+f"(d[3]), "+f"(d[4]), "+f"(d[5]), "+f"(d[6]), "+f"(d[7]),
          "+f"(d[8]), "+f"(d[9]), "+f"(d[10]), "+f"(d[11]), "+f"(d[12]), "+f"(d[13]), "+f"(d[14]), "+f"(d[15]),
          "+f"(d[16]), "+f"(d[17]), "+f"(d[18]), "+f"(d[19]), "+f"(d[20]), "+f"(d[21]), "+f"(d[22]), "+f"(d[23]),
          "+f"(d[24]), "+f"(d[25]), "+f"(d[26]), "+f"(d[27]), "+f"(d[28]), "+f"(d[29]), "+f"(d[30]), "+f"(d[31]),
          "+f"(d[32]), "+f"(d[33]), "+f"(d[34]), "+f"(d[35]), "+f"(d[36]), "+f"(d[37]), "+f"(d[38]), "+f"(d[39]),
          "+f"(d[40]), "+f"(d[41]), "+f"(d[42]), "+f"(d[43]), "+f"(d[44]), "+f"(d[45]), "+f"(d[46]), "+f"(d[47]),
          "+f"(d[48]), "+f"(d[49]), "+f"(d[50]), "+f"(d[51]), "+f"(d[52]), "+f"(d[53]), "+f"(d[54]), "+f"(d[55]),
          "+f"(d[56]), "+f"(d[57]), "+f"(d[58]), "+f"(d[59]), "+f"(d[60]), "+f"(d[61]), "+f"(d[62]), "+f"(d[63]),
          "+f"(d[64]), "+f"(d[65]), "+f"(d[66]), "+f"(d[67]), "+f"(d[68]), "+f"(d[69]), "+f"(d[70]), "+f"(d[71]),
          "+f"(d[72]), "+f"(d[73]), "+f"(d[74]), "+f"(d[75]), "+f"(d[76]), "+f"(d[77]), "+f"(d[78]), "+f"(d[79])
        : "l"(da), "l"(db), "r"(scale_d), "n"(TA), "n"(TB));
}
template <int TA, int TB>
__device__ __forceinline__ void wgmma80(float (&d)[40], uint64_t da, uint64_t db, int scale_d) {
    asm volatile(
        "{\n.reg .pred p;\nsetp.ne.b32 p, %42, 0;\n"
        "wgmma.mma_async.sync.aligned.m64n80k16.f32.bf16.bf16 "
        "{%0, %1, %2, %3, %4, %5, %6, %7, %8, %9, %10, %11, %12, %13, %14, %15, %16, %17, %18, %19, "
        "%20, %21, %22, %23, %24, %25, %26, %27, %28, %29, %30, %31, %32, %33, %34, %35, %36, %37, %38, %39}, "
        "%40, %41, p, 1, 1, %43, %44;\n}\n"
        : "+f"(d[0]), "+f"(d[1]), "+f"(d[2]), "+f"(d[3]), "+f"(d[4]), "+f"(d[5]), "+f"(d[6]), "+f"(d[7]),
          "+f"(d[8]), "+f"(d[9]), "+f"(d[10]), "+f"(d[11]), "+f"(d[12]), "+f"(d[13]), "+f"(d[14]), "+f"(d[15]),
          "+f"(d[16]), "+f"(d[17]), "+f"(d[18]), "+f"(d[19]), "+f"(d[20]), "+f"(d[21]), "+f"(d[22]), "+f"(d[23]),
          "+f"(d[24]), "+f"(d[25]), "+f"(d[26]), "+f"(d[27]), "+f"(d[28]), "+f"(d[29]), "+f"(d[30]), "+f"(d[31]),
          "+f"(d[32]), "+f"(d[33]), "+f"(d[34]), "+f"(d[35]), "+f"(d[36]), "+f"(d[37]), "+f"(d[38]), "+f"(d[39])
        : "l"(da), "l"(db), "r"(scale_d), "n"(TA), "n"(TB));
}
__device__ __forceinline__ uint32_t pack_bf16(float lo, float hi) {
    uint32_t r;
    asm("cvt.rn.bf16x2.f32 %0, %1, %2;" : "=r"(r) : "f"(hi), "f"(lo));
    return r;
}
__device__ __forceinline__ uint32_t hadd2(uint32_t a, uint32_t b) {
    uint32_t r;
    asm("add.rn.bf16x2 %0, %1, %2;" : "=r"(r) : "r"(a), "r"(b));
    return r;
}
__device__ __forceinline__ void lsum(float& l, const uint32_t* w) {
    const uint32_t t = hadd2(hadd2(hadd2(w[0], w[1]), hadd2(w[2], w[3])), hadd2(hadd2(w[4], w[5]), hadd2(w[6], w[7])));
    l += __uint_as_float(t << 16) + __uint_as_float(t & 0xffff0000u);
}
__device__ __forceinline__ float ex2(float x) {
    float r;
    asm("ex2.approx.ftz.f32 %0, %1;" : "=f"(r) : "f"(x));
    return r;
}
__device__ __forceinline__ void stsm4t(uint32_t addr, uint32_t a, uint32_t b, uint32_t c, uint32_t d) {
    asm volatile("stmatrix.sync.aligned.m8n8.x4.trans.shared.b16 [%0], {%1, %2, %3, %4};"
                 ::"r"(addr), "r"(a), "r"(b), "r"(c), "r"(d) : "memory");
}
__device__ __forceinline__ void stg128(void* p, uint32_t a, uint32_t b, uint32_t c, uint32_t d) {
    asm volatile("st.global.v4.u32 [%0], {%1, %2, %3, %4};" ::"l"(p), "r"(a), "r"(b), "r"(c), "r"(d) : "memory");
}

template <int TB> struct PB;
template <> struct PB<0> { static constexpr uint32_t LBO = 16, STEP = 32; };
template <> struct PB<1> { static constexpr uint32_t LBO = 2048, STEP = 1024; };

template <int W, int TB, int cont = 1>
__device__ __forceinline__ void quad_shared(float (&a0)[80], float (&a1)[80], uint32_t par, bool leader, bool rel0 = true) {
    static_for<4>([&](auto I) {
        constexpr uint32_t i = I.value;
        constexpr uint32_t rel = sb + B_PREMPTY + 8 * ((i + 3) & 3);
        const uint64_t da = mkdesc<16, 2048, 1>(sb + i * PR_BYTES);
        const uint64_t db = mkdesc<PB<TB>::LBO, 512, 2>(sb + i * PR_BYTES + 8192);
        constexpr int acc = i == 0 ? cont : 1;
        const bool dorel = leader && (i != 0 || (cont && rel0));
        constexpr int W0 = W < 10 ? W : W / 1000, W1 = W < 10 ? W : W / 100 % 10, W2 = W < 10 ? W : W / 10 % 10, W3 = W % 10;
        constexpr int RP = W0 <= 1 ? 0 : (W1 <= 2 ? 1 : (W2 <= 3 ? 2 : 3));
        mbar_wait(sb + B_PRFULL + 8 * i, par);
        wg_wait<W0 - 1>();
        if (RP == 0 && dorel) mbar_arrive(rel);
        wg_fence();
        wgmma160<1, TB>(a0, da, db, acc);
        wg_commit();
        wg_wait<W1 - 1>();
        if (RP == 1 && dorel) mbar_arrive(rel);
        wgmma160<1, TB>(a1, da + (1024 >> 4), db, acc);
        wg_commit();
        wg_wait<W2 - 1>();
        if (RP == 2 && dorel) mbar_arrive(rel);
        wgmma160<1, TB>(a0, da + (4096 >> 4), db + (PB<TB>::STEP >> 4), 1);
        wg_commit();
        wg_wait<W3 - 1>();
        if (RP == 3 && dorel) mbar_arrive(rel);
        wgmma160<1, TB>(a1, da + (5120 >> 4), db + (PB<TB>::STEP >> 4), 1);
        wg_commit();
    });
}
__device__ __forceinline__ void quad_alone(float (&a0)[80], float (&a1)[80], uint32_t base, uint32_t par, uint32_t pbase,
                                           int cont, bool leader) {
    const uint64_t da0 = mkdesc<16, 2048, 1>(sb) + base * (PR_BYTES >> 4);
    const uint64_t db0 = mkdesc<16, 512, 2>(sb + 8192) + base * (PR_BYTES >> 4);
    static_for<4>([&](auto I) {
        constexpr uint32_t i = I.value;
        const uint64_t da = da0 + i * (PR_BYTES >> 4), db = db0 + i * (PR_BYTES >> 4);
        const int acc = i == 0 ? cont : 1;
        mbar_wait(sb + B_PRFULL + 8 * i + 8 * base, par);
        wg_fence();
        wgmma160<1, 0>(a0, da, db, acc);
        wgmma160<1, 0>(a1, da + (1024 >> 4), db, acc);
        wgmma160<1, 0>(a0, da + (4096 >> 4), db + (32 >> 4), 1);
        wgmma160<1, 0>(a1, da + (5120 >> 4), db + (32 >> 4), 1);
        wg_commit();
        wg_wait<2>();
        if (leader && (i >= 2 || cont)) mbar_arrive(sb + B_PREMPTY + 8 * ((i + 2) & 3) + 8 * (i < 2 ? pbase : base));
    });
}

constexpr float QSCALE = 0.08838834764831845f * 1.4426950408889634f;

__device__ __forceinline__ uint32_t packq(float a, float b) { return pack_bf16(a * QSCALE, b * QSCALE); }
__device__ __forceinline__ float rbf(float x) { return __uint_as_float(pack_bf16(x, 0.f) << 16); }

__device__ __noinline__ void slow_head(const __nv_bfloat16* xp, const __nv_bfloat16* wp, const __nv_bfloat16* kp,
                                       const __nv_bfloat16* vp, unsigned char* os, int warp, int lane) {
    for (int qn = warp; qn < SQ; qn += 4) {
        float q[4] = {0.f, 0.f, 0.f, 0.f}, o[4] = {0.f, 0.f, 0.f, 0.f};
#pragma unroll 8
        for (int k = 0; k < 1024; k++) {
            const float xv = __bfloat162float(xp[qn * 1024 + k]);
            const uint2 w = __ldg(reinterpret_cast<const uint2*>(wp + (size_t)k * 4096 + 4 * lane));
            q[0] += xv * __uint_as_float(w.x << 16);
            q[1] += xv * __uint_as_float(w.x & 0xffff0000u);
            q[2] += xv * __uint_as_float(w.y << 16);
            q[3] += xv * __uint_as_float(w.y & 0xffff0000u);
        }
#pragma unroll
        for (int u = 0; u < 4; u++) q[u] = rbf(q[u]);
        float m = -INFINITY, l = 0.f;
        for (int key = 0; key < SK; key += 4) {
            float s[4];
            uint2 vv[4];
#pragma unroll
            for (int u = 0; u < 4; u++) {
                const uint2 kk = __ldg(reinterpret_cast<const uint2*>(kp + (key + u) * 128 + 4 * lane));
                vv[u] = __ldg(reinterpret_cast<const uint2*>(vp + (key + u) * 128 + 4 * lane));
                s[u] = q[0] * __uint_as_float(kk.x << 16) + q[1] * __uint_as_float(kk.x & 0xffff0000u) +
                       q[2] * __uint_as_float(kk.y << 16) + q[3] * __uint_as_float(kk.y & 0xffff0000u);
            }
#pragma unroll
            for (int off = 16; off; off >>= 1) {
#pragma unroll
                for (int u = 0; u < 4; u++) s[u] += __shfl_xor_sync(0xffffffffu, s[u], off);
            }
#pragma unroll
            for (int u = 0; u < 4; u++) s[u] = rbf(rbf(s[u]) * 0.08838834764831845f) * 1.4426950408889634f;
            const float mn = fmaxf(fmaxf(m, fmaxf(s[0], s[1])), fmaxf(s[2], s[3]));
            const float mref = (mn == -INFINITY) ? 0.f : mn;
            const float corr = exp2f(m - mref);
            m = mn;
            l *= corr;
            o[0] *= corr; o[1] *= corr; o[2] *= corr; o[3] *= corr;
#pragma unroll
            for (int u = 0; u < 4; u++) {
                const float pw = exp2f(s[u] - mref);
                l += pw;
                o[0] += pw * __uint_as_float(vv[u].x << 16);
                o[1] += pw * __uint_as_float(vv[u].x & 0xffff0000u);
                o[2] += pw * __uint_as_float(vv[u].y << 16);
                o[3] += pw * __uint_as_float(vv[u].y & 0xffff0000u);
            }
        }
        const float inv = 1.f / l;
#pragma unroll
        for (int u = 0; u < 4; u++) {
            const int d = 4 * lane + u;
            unsigned short* a = reinterpret_cast<unsigned short*>(
                os + (d >> 5) * 10240 + (qn >> 5) * 2048 + (d & 31) * 64 + ((((qn & 31) >> 3) ^ ((d & 7) >> 1)) << 4) + (qn & 7) * 2);
            *a = (unsigned short)(pack_bf16(o[u] * inv, 0.f) & 0xffffu);
        }
    }
}

#define CTA_COORDS()                                   \
    int cta;                                           \
    asm volatile("mov.u32 %0, %ctaid.x;" : "=r"(cta)); \
    const int g = cta >> 3, j = cta & 7, br = cta >> 6, b = g & 7; \
    (void)g; (void)j; (void)br; (void)b

__global__ void __launch_bounds__(512, 1) mha_fused_kernel(const __grid_constant__ Params prm) {
    extern __shared__ __align__(1024) unsigned char smem_raw[];
    if ((uint32_t)__cvta_generic_to_shared(smem_raw) != sb) __trap();
    const int wg = __shfl_sync(0xffffffffu, threadIdx.x >> 7, 0);
    const int lane = threadIdx.x & 31;

    if ((threadIdx.x >> 5) == 2) {
        if (elect_one()) {
            CTA_COORDS();
#pragma unroll
            for (int i = 0; i < 12; i++) mbar_init(sb + B_PRFULL + 8 * i, 1);
            asm volatile("fence.mbarrier_init.release.cluster;" ::: "memory");
            asm volatile("fence.proxy.async.shared::cta;" ::: "memory");
#pragma unroll 1
            for (int n = 0; n < NPRE; n++) {
                const uint32_t s = (8 - (n & 12)) + (n & 3);
                mbar_expect(sb + B_PRFULL + 8 * s, PR_BYTES);
                tmaw(sb + s * PR_BYTES, &prm.wq[br], n * 32, 2 * j, sb + B_PRFULL + 8 * s);
                tma2(sb + s * PR_BYTES + 8192, &prm.x[br], n * 32, b * SQ, sb + B_PRFULL + 8 * s);
            }
        }
        __syncwarp();
    } else if (threadIdx.x >= 128 && lane < 8) {
        const uint32_t a = SM_BAR + 8 * ((threadIdx.x >> 5) - 4 + 12 * lane);
        const bool one = a < B_KEMPTY || (a >= B_VFULL && a < B_VEMPTY) || (a >= B_QFULL && a < B_QREADY) ||
                         (a >= B_QVIS && a < B_PREMPTY) || (a >= B_ORDY && a < B_KVGO);
        if (a < B_PRFULL || a >= B_PREMPTY) mbar_init(sb + a, one ? 1 : 4);
        asm volatile("fence.mbarrier_init.release.cluster;" ::: "memory");
        asm volatile("fence.proxy.async.shared::cta;" ::: "memory");
    }
    __syncthreads();

    if (wg == 0) {
        asm volatile("setmaxnreg.dec.sync.aligned.u32 24;");
        const int warp = __shfl_sync(0xffffffffu, warp_now(), 0);
        if (warp == 0) {
            if (elect_one()) {
                CTA_COORDS();
                const int row0 = (b * NH + j) * SK;
                mbar_wait(sb + B_KVGO, 0);
#pragma unroll 1
                for (int t = 0; t < 65; t++) {
                    if (t < 64) {
                        const uint32_t s = t & 1;
                        const bool newq = (t & 15) == 1 && t > 1;
                        const unsigned char* qsrc = g_scr + (size_t)(g * 32 + ((t >> 4) - 1) * 8 + j) * 40960;
                        if (newq) {
                            mbar_wait(sb + B_QVIS + 8 * (t >> 4), 0);
                            mbar_wait(sb + B_QFREE, ((t >> 4) & 1) ^ 1);
                            mbar_expect(sb + B_QFULL, 20480);
                            bulk_g2s(sb + SM_Q, qsrc, 20480, sb + B_QFULL);
                        }
                        mbar_wait(sb + B_KEMPTY + 8 * s, ((t >> 1) & 1) ^ 1);
                        if (newq) {
                            mbar_expect(sb + B_QFULL + 8, 20480);
                            bulk_g2s(sb + SM_Q + 20480, qsrc + 20480, 20480, sb + B_QFULL + 8);
                        }
                        mbar_expect(sb + B_KFULL + 8 * s, 16384);
                        tma4_hint(sb + SM_K + s * 16384, &prm.k[br], (row0 + (t >> 4) * (8 * SK) + (t & 15) * 64) >> 3,
                                  sb + B_KFULL + 8 * s, POL_EF);
                    }
#pragma unroll 1
                    for (int u = t == 2 ? 2 : t - 1; u >= 0 && u < (t == 1 ? 2 : t); u++) {
                        const uint32_t s = u & 1;
                        mbar_wait(sb + B_VEMPTY + 8 * s, ((u >> 1) & 1) ^ 1);
                        mbar_expect(sb + B_VFULL + 8 * s, 16384);
                        tma4_hint(sb + SM_V + s * 16384, &prm.v[br], (row0 + (u >> 4) * (8 * SK) + (u & 15) * 64) >> 3,
                                  sb + B_VFULL + 8 * s, POL_EF);
                    }
                }
            }
        } else if (warp == 1) {
            if (lane == 0) {
                CTA_COORDS();
                const unsigned int target = g_epoch[cta] + 1;
#pragma unroll 1
                for (int r = 0; r < 4; r++) {
                    mbar_wait(sb + B_ODONE + 8 * r, 0);
                    asm volatile("st.release.gpu.global.u32 [%0], %1;" ::"l"(g_flag + g * 32 + r * 8 + j), "r"(target) : "memory");
                }
            }
        } else if (warp == 2) {
            if (elect_one()) {
                CTA_COORDS();
                int pf = 8 + (b >> 2);
#pragma unroll 1
                for (int n = NPRE; n < 12; n++) {
                    const uint32_t s = (8 - (n & 12)) + (n & 3);
                    mbar_expect(sb + B_PRFULL + 8 * s, PR_BYTES);
                    tmaw(sb + s * PR_BYTES, &prm.wq[br], n * 32, 2 * j, sb + B_PRFULL + 8 * s);
                    tma2(sb + s * PR_BYTES + 8192, &prm.x[br], n * 32, b * SQ, sb + B_PRFULL + 8 * s);
                }
                auto load_q = [&](int q, uint32_t base, uint32_t par) {
                    const uint32_t dst = sb + base * PR_BYTES, bar = sb + B_PRFULL + 8 * base;
                    const int k0 = (q & 7) * 128, hc = 2 * ((q >> 3) * 8 + j);
#pragma unroll
                    for (int i = 0; i < 4; i++) {
                        mbar_wait(bar + (B_PREMPTY - B_PRFULL) + 8 * i, par ^ 1);
                        tma2(dst + i * PR_BYTES + 8192, &prm.x[br], k0 + i * 32, b * SQ, bar + 8 * i);
                        tmaw(dst + i * PR_BYTES, &prm.wq[br], k0 + i * 32, hc, bar + 8 * i);
                        mbar_expect(bar + 8 * i, PR_BYTES);
                    }
                    const int mend = q <= 8 ? 8 + HP * (q - 2) : q + PDQ + 1;
#pragma unroll 1
                    for (; pf < mend; pf += 2) {
                        if (pf < 32) pfw(&prm.wq[br], (pf & 7) * 128 + (b & 3) * 32, 2 * ((pf >> 3) * 8 + j));
                        else pfw(&prm.wo[br], (pf - 32) * 128 + (b & 3) * 32, 2 * j);
                    }
                };
#pragma unroll 1
                for (int q = 3; q < 8; q++) load_q(q, 4 * (q & 1), ((q - 1) >> 1) & 1);
#pragma unroll 1
                for (int q = 8; q < 32; q++) load_q(q, 0, (q + 1) & 1);
                const unsigned char* osrc = g_scr + (size_t)g * (128 * 10240);
                auto load_o = [&](int q, auto BASE) {
                    constexpr uint32_t dst = sb + BASE.value * PR_BYTES, bar = sb + B_PRFULL + 8 * BASE.value;
                    mbar_wait(sb + B_ORDY + 8 * q, 0);
                    uint32_t hh;
                    asm volatile("ld.shared.u8 %0, [%1];" : "=r"(hh) : "r"(sb + SM_ORD + q) : "memory");
#pragma unroll
                    for (int i = 0; i < 4; i++) {
                        if (BASE.value == 0) mbar_wait(sb + B_PREMPTY + 8 * i, q & 1);
                        tmaw(dst + i * PR_BYTES, &prm.wo[br], hh * 128 + i * 32, 2 * j, bar + 8 * i);
                        bulk_g2s(dst + i * PR_BYTES + 8192, osrc + hh * 40960 + i * 10240, 10240, bar + 8 * i);
                        mbar_expect(bar + 8 * i, PR_BYTES);
                    }
                };
#pragma unroll 1
                for (int q = 0; q < 31; q++) {
                    load_o(q, IC<0>{});
                    const int m = q + PDQ;
                    if (m < 24 && (m & 1) == (b >> 2)) pfw(&prm.wo[br], m * 128 + (b & 3) * 32, 2 * j);
                }
                load_o(31, IC<8>{});
            }
        } else {
            CTA_COORDS();
            const unsigned int target = g_epoch[cta] + 1;
            if (lane == 0) {
#pragma unroll 1
                for (int r = 1; r < 4; r++) {
                    mbar_wait_lim(sb + B_QREADY + 8 * r, 0);
                    asm volatile("fence.acq_rel.gpu;" ::: "memory");
                    asm volatile("fence.proxy.async.global;" ::: "memory");
                    mbar_arrive(sb + B_QVIS + 8 * r);
                    if (r == 2) break;
                }
            }
            __syncwarp();
            int nr = 0;
            unsigned int seen = 0;
            bool q3 = false;
            unsigned int it = 0;
            while (nr < 32) {
                if (!q3 && mbar_test(sb + B_QREADY + 24, 0)) {
                    if (lane == 0) {
                        asm volatile("fence.acq_rel.gpu;" ::: "memory");
                        asm volatile("fence.proxy.async.global;" ::: "memory");
                        mbar_arrive(sb + B_QVIS + 24);
                    }
                    q3 = true;
                }
                unsigned int v;
                asm volatile("ld.acquire.gpu.global.u32 %0, [%1];" : "=r"(v) : "l"(g_flag + g * 32 + lane) : "memory");
                unsigned int fresh = __ballot_sync(0xffffffffu, v == target);
                fresh &= ~seen;
                if (fresh) {
                    asm volatile("fence.proxy.async.global;" ::: "memory");
                    if ((fresh >> lane) & 1) {
                        const uint32_t pos = nr + __popc(fresh & ((1u << lane) - 1));
                        asm volatile("st.shared.u8 [%0], %1;" ::"r"(sb + SM_ORD + pos), "r"(lane) : "memory");
                        mbar_arrive(sb + B_ORDY + 8 * pos);
                    }
                    nr += __popc(fresh);
                    seen |= fresh;
                }
                if (nr < 24) __nanosleep(400);
                else if (!mbar_test(sb + B_ADONE, 0)) __nanosleep(150);
                if (++it > 8388608u) __trap();
                __syncwarp();
            }
            if (lane == 0) g_epoch[cta] = target;
            mbar_wait_lim(sb + B_END, 0);
        }
    } else if (wg == 1) {
        asm volatile("setmaxnreg.dec.sync.aligned.u32 104;");
        float s[40], x[40];
#pragma unroll
        for (int i = 0; i < 40; i++) s[i] = x[i] = 0.f;
        const uint32_t t8 = lane & 7, m = lane >> 3;
        const uint32_t pst = sb + SM_P + (8 * (m >> 1) + t8) * 128 + (((2 * warp_now() + (m & 1)) ^ t8) << 4);
        auto qk = [&](uint32_t sl, int hf) {
            const uint64_t da = mkdesc<16, 2048, 1>(sb + SM_K + sl * 16384);
            const uint64_t db = mkdesc<4096, 256, 3>(sb + SM_Q + hf * 20480);
            wg_fence();
#pragma unroll
            for (int kk = 0; kk < 8; kk++)
                wgmma80<0, 1>(s, da + (((kk >> 2) * 1024 + (kk & 3) * 32) >> 4), db + ((kk * 512) >> 4), kk != 0 ? 1 : prm.zero);
            wg_commit();
        };
        auto stage = [&](int dir) {
            wg_wait<0>();
            acc_fence(s);
#pragma unroll
            for (int i = 0; i < 40; i++) x[i] = i < dir ? ex2(s[i]) : s[i] * prm.one;
            acc_fence(x);
        };
        auto expo = [&](uint32_t pa, int jj, int dir) {
            auto e = [&](int i) { return i < dir ? x[i] : ex2(x[i]); };
            stsm4t(pa + jj * 2048, pack_bf16(e(8 * jj), e(8 * jj + 1)), pack_bf16(e(8 * jj + 2), e(8 * jj + 3)),
                   pack_bf16(e(8 * jj + 4), e(8 * jj + 5)), pack_bf16(e(8 * jj + 6), e(8 * jj + 7)));
        };
        mbar_wait(sb + B_QREADY, 0);
        mbar_wait(sb + B_KFULL, 0);
        qk(0, 0);
#pragma unroll 1
        for (int t2 = 0; t2 < 32; t2++) {
            const uint32_t ph = t2 & 1;
            static_for<2>([&](auto SL) {
                constexpr uint32_t sl = SL.value;
                const uint32_t pa = pst + sl * P_BYTES;
                const bool last = sl == 1 && (t2 & 7) == 7;
                if (last) {
                    wg_wait<0>();
                    mbar_arrive_warp(sb + B_QFREE);
                }
                stage(DIRA);
                if (sl == 0 && (t2 & 7) == 0 && t2 != 0) mbar_wait(sb + B_QFULL + 8, ((t2 >> 3) & 1) ^ 1);
                qk(sl, 1);
                mbar_wait(sb + B_PEMPTY + 8 * sl, ph ^ 1);
                SCHED_FENCE(t2, 1 + sl);
#pragma unroll
                for (int jj = 0; jj < 5; jj++) expo(pa, jj, DIRA);
                wg_wait<0>();
                mbar_arrive_warp(sb + B_KEMPTY + 8 * sl);
                stage(DIRB);
#pragma unroll
                for (int jj = 0; jj < DIRB / 8; jj++) expo(pa + 10240, jj, DIRB);
                if (!last) {
                    mbar_wait_lim(sb + B_KFULL + 8 * (sl ^ 1), sl == 0 ? ph : ph ^ 1);
                    qk(sl ^ 1, 0);
                    if (sl == 0) SCHED_FENCE(t2, 0);
                }
#pragma unroll
                for (int jj = DIRB / 8; jj < 5; jj++) expo(pa + 10240, jj, DIRB);
                asm volatile("fence.acq_rel.cta;" ::: "memory");
                __syncwarp();
                mbar_arrive_warp(sb + B_PFULL + 8 * sl);
                if (last && t2 != 31) {
                    mbar_wait(sb + B_QFULL, (t2 >> 3) & 1);
                    mbar_wait(sb + B_KFULL, ph ^ 1);
                    qk(0, 0);
                }
            });
        }
        wg_wait<0>();
    } else if (wg == 2) {
        asm volatile("setmaxnreg.inc.sync.aligned.u32 192;");
        float o0[80], o1[80];
        const uint32_t prow = warp_now() * 8 + (lane >> 2);
        const uint32_t pld = prow * 128 + (((lane & 3) | ((prow & 1) << 2)) << 4);
#pragma unroll 1
        for (int r = 0; r < 4; r++) {
            float l[5] = {0.f, 0.f, 0.f, 0.f, 0.f};
            bool bad = false;
            auto pv_begin = [&](auto SL, auto ACC, uint32_t ph) {
                constexpr uint32_t sl = SL.value;
                mbar_wait(sb + B_VFULL + 8 * sl, ph);
                mbar_wait(sb + B_PFULL + 8 * sl, ph);
                asm volatile("fence.proxy.async.shared::cta;" ::: "memory");
                wg_fence();
                wgmma160<1, 0>(o0, mkdesc<16, 2048, 1>(sb + SM_V + sl * 16384), mkdesc<16, 1024, 1>(sb + SM_P + sl * P_BYTES), ACC.value);
                wg_commit();
                wgmma160<1, 0>(o1, mkdesc<16, 2048, 1>(sb + SM_V + sl * 16384 + 1024), mkdesc<16, 1024, 1>(sb + SM_P + sl * P_BYTES), ACC.value);
                wg_commit();
            };
            pv_begin(IC<0>{}, IC<0>{}, 0);
#pragma unroll 1
            for (int i2 = 0; i2 < 8; i2++) static_for<2>([&](auto SL) {
                constexpr uint32_t sl = SL.value;
                const uint64_t da = mkdesc<16, 2048, 1>(sb + SM_V + sl * 16384);
                const uint64_t db = mkdesc<16, 1024, 1>(sb + SM_P + sl * P_BYTES);
                if (sl == 0) wg_fence();
                uint32_t w[8];
                static_for<8, 2>([&](auto K) {
                    constexpr int k = K.value;
                    if constexpr (k >= PVW) wg_wait<PVW - 1>();
                    if constexpr (k >= 3) wg_fence();
                    if (k & 1) wgmma160<1, 0>(o1, da + ((1024 + (k >> 1) * 4096) >> 4), db + (((k >> 1) * 32) >> 4), 1);
                    else wgmma160<1, 0>(o0, da + (((k >> 1) * 4096) >> 4), db + (((k >> 1) * 32) >> 4), 1);
                    wg_commit();
                    if constexpr (k >= 3) lsum(l[k - 3], w);
                    if constexpr (k < 7) {
                        lds128u<sb + SM_P + sl * P_BYTES + (k - 2) * 4096>(pld, w);
                        lds128u<sb + SM_P + sl * P_BYTES + (k - 2) * 4096>(pld ^ 64, w + 4);
                        SCHED_FENCE(i2, k + 8 * sl);
                    }
                });
                if (sl == 1 && i2 == 7) {
#pragma unroll
                    for (int k = 0; k < 5; k++) l[k] += __shfl_xor_sync(0xffffffffu, l[k], 1);
#pragma unroll
                    for (int k = 0; k < 5; k++) l[k] += __shfl_xor_sync(0xffffffffu, l[k], 2);
                    const uint32_t ln = lane_now();
                    const uint32_t la = sb + SM_LINV + (((ln >> 3) & 3) * 8 + warp_now() * 2 + ((ln >> 2) & 1)) * 4;
#pragma unroll
                    for (int k = 0; k < 5; k++) {
                        bad |= !(l[k] >= 0.00390625f && l[k] <= 4294967296.f);
                        float v;
                        asm("rcp.approx.ftz.f32 %0, %1;" : "=f"(v) : "f"(l[k]));
                        if ((ln & 3) == 0) asm volatile("st.shared.f32 [%0], %1;" ::"r"(la + 128 * k), "f"(v) : "memory");
                    }
                }
                wg_wait<0>();
                __syncwarp();
                mbar_arrive_warp(sb + B_VEMPTY + 8 * sl);
                mbar_arrive_warp(sb + B_PEMPTY + 8 * sl);
                if (sl == 0) pv_begin(IC<1>{}, IC<1>{}, i2 & 1);
                else if (i2 != 7) pv_begin(IC<0>{}, IC<1>{}, (i2 & 1) ^ 1);
            });
            wg_wait<0>();
            if (r == 3) mbar_arrive_warp(sb + B_ADONE);
            acc_fence(o0);
            acc_fence(o1);
            uint32_t redo;
            asm volatile("{\n.reg .pred p, q;\nsetp.ne.u32 p, %1, 0;\nbar.red.or.pred q, 1, 128, p;\nselp.u32 %0, 1, 0, q;\n}"
                         : "=r"(redo) : "r"((uint32_t)bad) : "memory");
            if (r < 3) mbar_wait(sb + B_QFULL, r & 1);
            CTA_COORDS();
            unsigned char* os = g_scr + (size_t)(g * 32 + 8 * r + j) * 40960;
            if (__any_sync(0xffffffffu, redo)) {
                const int h = 8 * r + j;
                if (r < 3) mbar_wait(sb + B_QFULL + 8, r & 1);
                slow_head(prm.xp[br] + (size_t)b * SQ * 1024, prm.wqp[br] + h * 128, prm.kp[br] + (size_t)(b * NH + h) * SK * 128,
                          prm.vp[br] + (size_t)(b * NH + h) * SK * 128, os, warp_now(), lane_now());
            } else {
                const uint32_t ln = lane_now(), g8 = ln >> 2, warp = warp_now();
                unsigned char* op = os + (warp >> 1) * 10240 + (16 * (warp & 1) + g8) * 64 + (((ln & 3) ^ (g8 >> 1)) << 4);
                const uint32_t li = (ln & 3) * 32;
                float iv[40];
                lds128i<sb + SM_LINV>(li, iv);
                lds128i<sb + SM_LINV + 16>(li, iv + 4);
                auto put = [&](const float* o, const float* v, unsigned char* p) {
                    stg128(p, pack_bf16(o[0] * v[0], o[1] * v[1]), pack_bf16(o[4] * v[2], o[5] * v[3]),
                           pack_bf16(o[8] * v[4], o[9] * v[5]), pack_bf16(o[12] * v[6], o[13] * v[7]));
                };
                static_for<5>([&](auto I) {
                    constexpr int i = I.value;
                    if constexpr (i < 4) {
                        lds128i<sb + SM_LINV + 128 * (i + 1)>(li, iv + 8 * (i + 1));
                        lds128i<sb + SM_LINV + 128 * (i + 1) + 16>(li, iv + 8 * (i + 1) + 4);
                    }
                    put(o0 + 16 * i, iv + 8 * i, op + i * 2048);
                    put(o0 + 16 * i + 2, iv + 8 * i, op + i * 2048 + 512);
                });
                if (r < 3) mbar_wait(sb + B_QFULL + 8, r & 1);
                static_for<5>([&](auto I) {
                    constexpr int i = I.value;
                    put(o1 + 16 * i, iv + 8 * i, op + 20480 + i * 2048);
                    put(o1 + 16 * i + 2, iv + 8 * i, op + 20480 + i * 2048 + 512);
                });
            }
            __syncwarp();
            mbar_arrive_warp(sb + B_ODONE + 8 * r);
        }
    } else {
        asm volatile("setmaxnreg.inc.sync.aligned.u32 192;");
        float a0[80], a1[80];
        const bool leader = lane == 0;
        {
            uint32_t pbase = 0;
#pragma unroll 1
            for (int q = 0; q < 8; q++) {
                const uint32_t base = q == 0 ? 8 : 4 * (q & 1), par = q == 0 ? 0 : ((q - 1) >> 1) & 1;
                if (leader && q == KV_START) mbar_arrive(sb + B_KVGO);
                quad_alone(a0, a1, base, par, pbase, q, leader);
                pbase = base;
            }
            const uint32_t ln = lane_now(), g8 = ln >> 2;
            const uint32_t qo = ((ln >> 1) & 1) * 4096 + (16 * warp_now() + g8) * 32 + (((ln & 1) ^ (g8 >> 2)) << 4);
            wg_wait<0>();
            acc_fence(a0);
            acc_fence(a1);
            asm volatile("bar.sync 2, 128;" ::: "memory");
            static_for<20>([&](auto I) {
                constexpr int i = I.value, a = 16 * (i >> 2) + 2 * (i & 1);
                const float* v = (i & 2) ? a1 : a0;
                sts128i<sb + SM_Q + (i >> 2) * 8192 + ((i >> 1) & 1) * 2048 + (i & 1) * 256>(
                    qo, packq(v[a], v[a + 1]), packq(v[a + 4], v[a + 5]), packq(v[a + 8], v[a + 9]), packq(v[a + 12], v[a + 13]));
            });
            asm volatile("fence.proxy.async.shared::cta;" ::: "memory");
            __syncwarp();
            mbar_arrive_warp(sb + B_QREADY);
        }
#pragma unroll 1
        for (int r = 1; r < 4; r++) {
            quad_shared<PWQ, 0, 0>(a0, a1, 1, leader);
#pragma unroll 1
            for (int q = 1; q < 8; q++) {
                quad_shared<PWQ, 0>(a0, a1, (q + 1) & 1, leader);
            }
            CTA_COORDS();
            const uint32_t ln = lane_now(), g8 = ln >> 2;
            unsigned char* qp = g_scr + (size_t)(g * 32 + (r - 1) * 8 + j) * 40960 + ((ln >> 1) & 1) * 4096 +
                                (16 * warp_now() + g8) * 32 + (((ln & 1) ^ (g8 >> 2)) << 4);
            wg_wait<0>();
            acc_fence(a0);
            acc_fence(a1);
            mbar_arrive_warp(sb + B_PREMPTY + 8 * 3);
#pragma unroll
            for (int i = 0; i < 20; i++) {
                const int a = 16 * (i >> 2) + 2 * (i & 1);
                const float* v = (i & 2) ? a1 : a0;
                stg128(qp + (i >> 2) * 8192 + ((i >> 1) & 1) * 2048 + (i & 1) * 256, packq(v[a], v[a + 1]),
                       packq(v[a + 4], v[a + 5]), packq(v[a + 8], v[a + 9]), packq(v[a + 12], v[a + 13]));
            }
            __syncwarp();
            mbar_arrive_warp(sb + B_QREADY + 8 * r);
        }
        bool alone = false;
        quad_shared<PWO, 1, 0>(a0, a1, 1, leader);
#pragma unroll 1
        for (int q = 33; q < 63; q++) {
            const bool rel0 = q < 48 || mbar_test(sb + B_ORDY + 8 * (q - 32), 0);
            if (!rel0) {
                wg_wait<0>();
                if (leader) mbar_arrive(sb + B_PREMPTY + 8 * 3);
            }
            if (!alone && q >= 48) {
                mbar_wait(sb + B_PRFULL, (q + 1) & 1);
                uint32_t a;
                asm volatile("{\n.reg .pred p, q;\nmbarrier.test_wait.parity.shared::cta.b64 p, [%1], 0;\n"
                             "bar.red.and.pred q, 2, 128, p;\nselp.u32 %0, 1, 0, q;\n}" : "=r"(a) : "r"(sb + B_ADONE) : "memory");
                alone = a != 0;
            }
            if (alone) quad_shared<PWT, 1>(a0, a1, (q + 1) & 1, leader, rel0);
            else quad_shared<PWO, 1>(a0, a1, (q + 1) & 1, leader, rel0);
        }
        const uint32_t ln = lane_now(), t8 = ln & 7, m = ln >> 3, warp = __shfl_sync(0xffffffffu, warp_now(), 0);
        const uint32_t pst = sb + SM_Q + (8 * (m >> 1) + t8) * 128 + (((2 * warp + (m & 1)) ^ t8) << 4);
        static_for<4>([&](auto I) {
            constexpr uint32_t a = sb + (8 + I.value) * PR_BYTES;
            mbar_wait(sb + B_PRFULL + 8 * (8 + I.value), 1);
            wg_fence();
            wgmma160<1, 1>(a0, mkdesc<16, 2048, 1>(a), mkdesc<2048, 512, 2>(a + 8192), 1);
            wgmma160<1, 1>(a0, mkdesc<16, 2048, 1>(a + 4096), mkdesc<2048, 512, 2>(a + 9216), 1);
            wg_commit();
        });
        static_for<4>([&](auto I) {
            constexpr uint32_t a = sb + (8 + I.value) * PR_BYTES;
            wgmma160<1, 1>(a1, mkdesc<16, 2048, 1>(a + 1024), mkdesc<2048, 512, 2>(a + 8192), 1);
            wgmma160<1, 1>(a1, mkdesc<16, 2048, 1>(a + 5120), mkdesc<2048, 512, 2>(a + 9216), 1);
        });
        wg_commit();
        auto put_half = [&](const float (&a)[80], auto H) {
            static_for<OCH>([&](auto C) {
                constexpr int c = C.value, per = 10 / OCH;
#pragma unroll
                for (int jj = c * per; jj < (c + 1) * per; jj++)
                    stsm4t(pst + H.value * P_BYTES + jj * 2048, pack_bf16(a[8 * jj], a[8 * jj + 1]), pack_bf16(a[8 * jj + 2], a[8 * jj + 3]),
                           pack_bf16(a[8 * jj + 4], a[8 * jj + 5]), pack_bf16(a[8 * jj + 6], a[8 * jj + 7]));
                asm volatile("fence.proxy.async.shared::cta;" ::: "memory");
                if (warp == (c & 3)) {
                    asm volatile("bar.sync %0, 128;" ::"n"(3 + (H.value * OCH + c) % 10) : "memory");
                    if (elect_one()) {
                        CTA_COORDS();
                        tma2_store(&prm.out, sb + SM_Q + H.value * P_BYTES + c * per * 2048, br * 1024 + j * 128 + H.value * 64,
                                   b * SQ + c * per * 16);
                        asm volatile("cp.async.bulk.commit_group;" ::: "memory");
                    }
                    __syncwarp();
                } else {
                    asm volatile("bar.arrive %0, 128;" ::"n"(3 + (H.value * OCH + c) % 10) : "memory");
                }
            });
        };
        wg_wait<1>();
        acc_fence(a0);
        put_half(a0, IC<0>{});
        wg_wait<0>();
        acc_fence(a1);
        mbar_arrive_warp(sb + B_END);
        put_half(a1, IC<1>{});
        asm volatile("cp.async.bulk.wait_group 0;" ::: "memory");
    }
}

typedef CUresult (*EncodeFn)(CUtensorMap*, CUtensorMapDataType, cuuint32_t, void*, const cuuint64_t*, const cuuint64_t*,
                             const cuuint32_t*, const cuuint32_t*, CUtensorMapInterleave, CUtensorMapSwizzle,
                             CUtensorMapL2promotion, CUtensorMapFloatOOBfill);

void encode(EncodeFn fn, CUtensorMap* m, void* p, int rank, const cuuint64_t* dims, const cuuint64_t* strides,
            const cuuint32_t* box, CUtensorMapSwizzle swz) {
    cuuint32_t es[4] = {1, 1, 1, 1};
    fn(m, CU_TENSOR_MAP_DATA_TYPE_BFLOAT16, rank, p, dims, strides, box, es, CU_TENSOR_MAP_INTERLEAVE_NONE, swz,
       CU_TENSOR_MAP_L2_PROMOTION_L2_128B, CU_TENSOR_MAP_FLOAT_OOB_FILL_NONE);
}

}


extern "C" void kernel_launch(void* const* d_in, const int* in_sizes, int n_in, void* d_out, int out_size) {
    static EncodeFn fn = nullptr;
    if (!fn) {
        void* f = nullptr;
        cudaDriverEntryPointQueryResult st;
        cudaGetDriverEntryPoint("cuTensorMapEncodeTiled", &f, cudaEnableDefault, &st);
        fn = (EncodeFn)f;
        cudaFuncSetAttribute(mha_fused_kernel, cudaFuncAttributeMaxDynamicSharedMemorySize, SM_TOTAL);
    }
    Params prm;
    prm.zero = 0;
    prm.one = 1.f;
    prm.never = 1 << 20;
    for (int br = 0; br < 2; br++) {
        void* x = d_in[5 * br + 0];
        void* k = d_in[5 * br + 1];
        void* v = d_in[5 * br + 2];
        void* wq = d_in[5 * br + 3];
        void* wo = d_in[5 * br + 4];
        {
            cuuint64_t dims[4] = {64, 8, 2, (cuuint64_t)NH * SK}, str[3] = {256, 128, 2048};
            cuuint32_t box[4] = {64, 8, 2, 8};
            encode(fn, &prm.k[br], k, 4, dims, str, box, CU_TENSOR_MAP_SWIZZLE_128B);
            encode(fn, &prm.v[br], v, 4, dims, str, box, CU_TENSOR_MAP_SWIZZLE_128B);
        }
        {
            cuuint64_t dims[4] = {64, 8, 64, 128}, str[3] = {8192, 128, 65536};
            cuuint32_t box[4] = {64, 8, 2, 4};
            encode(fn, &prm.wq[br], wq, 4, dims, str, box, CU_TENSOR_MAP_SWIZZLE_128B);
        }
        {
            cuuint64_t dims[4] = {64, 8, 16, 512}, str[3] = {2048, 128, 16384};
            cuuint32_t box[4] = {64, 8, 2, 4};
            encode(fn, &prm.wo[br], wo, 4, dims, str, box, CU_TENSOR_MAP_SWIZZLE_128B);
        }
        {
            cuuint64_t dims[2] = {1024, 1280}, str[1] = {2048};
            cuuint32_t box[2] = {32, 160};
            encode(fn, &prm.x[br], x, 2, dims, str, box, CU_TENSOR_MAP_SWIZZLE_64B);
        }
        prm.kp[br] = (const __nv_bfloat16*)k;
        prm.vp[br] = (const __nv_bfloat16*)v;
        prm.xp[br] = (const __nv_bfloat16*)x;
        prm.wqp[br] = (const __nv_bfloat16*)wq;
    }
    {
        cuuint64_t dims[2] = {2048, 1280}, str[1] = {4096};
        cuuint32_t box[2] = {64, 160 / OCH};
        encode(fn, &prm.out, d_out, 2, dims, str, box, CU_TENSOR_MAP_SWIZZLE_128B);
    }
    mha_fused_kernel<<<NCTA, 512, SM_TOTAL, cudaStreamPerThread>>>(prm);
}
```

```cpp
#include <cuda_runtime.h>
#include <cuda_bf16.h>
#include <cuda.h>
#include <stdint.h>

namespace {

constexpr int SQ = 160, SK = 1024, NH = 32;
constexpr int NCTA = 128;

constexpr uint32_t sb = 1024;
constexpr uint32_t PR_BYTES = 18432;
constexpr uint32_t SM_Q = 4 * PR_BYTES;
constexpr uint32_t SM_P = SM_Q + 40960;
constexpr uint32_t P_BYTES = 20480;
constexpr uint32_t SM_K = SM_P + 2 * P_BYTES;
constexpr uint32_t SM_V = SM_K + 2 * 16384;
constexpr uint32_t SM_LINV = SM_V + 2 * 16384;
constexpr uint32_t SM_BAR = SM_LINV + 160 * 4;
constexpr uint32_t SM_ORD = SM_BAR + 768;
constexpr uint32_t SM_TOTAL = SM_ORD + 32;
static_assert(SM_V + 2 * 16384 == 12 * PR_BYTES, "Q/P/K/V double as stage slots 4..11 before and after attention");
constexpr uint32_t B_KFULL = SM_BAR + 0;
constexpr uint32_t B_KEMPTY = SM_BAR + 16;
constexpr uint32_t B_VFULL = SM_BAR + 32;
constexpr uint32_t B_VEMPTY = SM_BAR + 48;
constexpr uint32_t B_PFULL = SM_BAR + 64;
constexpr uint32_t B_PEMPTY = SM_BAR + 80;
constexpr uint32_t B_QFULL = SM_BAR + 96;
constexpr uint32_t B_QREADY = SM_BAR + 112;
constexpr uint32_t B_ODONE = SM_BAR + 144;
constexpr uint32_t B_QVIS = SM_BAR + 176;
constexpr uint32_t B_PRFULL = SM_BAR + 208;
constexpr uint32_t B_PREMPTY = SM_BAR + 304;
constexpr uint32_t B_ORDY = SM_BAR + 400;
constexpr uint32_t B_KVGO = SM_BAR + 656;
constexpr uint32_t B_QFREE = SM_BAR + 672;
constexpr uint32_t B_ADONE = SM_BAR + 680;
constexpr uint32_t B_END = SM_BAR + 688;
constexpr int KV_START = 7;
constexpr int PDQ = 5;
constexpr int HP = 2;
constexpr int OCH = 2;
constexpr int DIRA = 8, DIRB = 20;
constexpr int PVW = 3;
constexpr int PWQ = 1212, PWO = 2, PWT = 4;

template <int V> struct IC { static constexpr int value = V; };
template <int N, int I = 0, class F> __device__ __forceinline__ void static_for(F&& f) {
    if constexpr (I < N) {
        f(IC<I>{});
        static_for<N, I + 1>(f);
    }
}

struct Params {
    CUtensorMap k[2], v[2], x[2], wq[2], wo[2], out;
    const __nv_bfloat16* kp[2];
    const __nv_bfloat16* vp[2];
    const __nv_bfloat16* xp[2];
    const __nv_bfloat16* wqp[2];
    int zero;
    float one;
    int never;
};

__device__ __align__(1024) unsigned char g_scr[16 * 32 * 40960];
__device__ __align__(128) unsigned int g_flag[16 * 32];
__device__ unsigned int g_epoch[NCTA];

__device__ __forceinline__ void mbar_init(uint32_t b, int c) {
    asm volatile("mbarrier.init.shared::cta.b64 [%0], %1;" ::"r"(b), "r"(c));
}
__device__ __forceinline__ void mbar_expect(uint32_t b, int bytes) {
    asm volatile("mbarrier.arrive.expect_tx.shared::cta.b64 _, [%0], %1;" ::"r"(b), "r"(bytes) : "memory");
}
__device__ __forceinline__ void mbar_arrive(uint32_t b) {
    asm volatile("mbarrier.arrive.shared::cta.b64 _, [%0];" ::"r"(b) : "memory");
}
__device__ __forceinline__ void mbar_arrive_warp(uint32_t b) {
    asm volatile("{\n.reg .pred p;\nelect.sync _|p, 0xffffffff;\n@p mbarrier.arrive.shared::cta.b64 _, [%0];\n}" ::"r"(b) : "memory");
}
__device__ __forceinline__ bool elect_one() {
    uint32_t r;
    asm volatile("{\n.reg .pred p;\nelect.sync _|p, 0xffffffff;\nselp.u32 %0, 1, 0, p;\n}" : "=r"(r));
    return r != 0;
}
__device__ __forceinline__ uint32_t warp_now() {
    uint32_t r;
    asm volatile("mov.u32 %0, %tid.x;" : "=r"(r));
    return (r >> 5) & 3;
}
__device__ __forceinline__ uint32_t lane_now() {
    uint32_t r;
    asm volatile("mov.u32 %0, %laneid;" : "=r"(r));
    return r;
}
__device__ __forceinline__ void mbar_wait(uint32_t b, uint32_t ph) {
    asm volatile("{\n.reg .pred p;\nW:\nmbarrier.try_wait.parity.shared::cta.b64 p, [%0], %1;\n@!p bra W;\n}" ::"r"(b), "r"(ph) : "memory");
}
__device__ __forceinline__ void mbar_wait_lim(uint32_t b, uint32_t ph) {
    asm volatile(
        "{\n.reg .pred p;\n.reg .u32 n;\n"
        "mbarrier.try_wait.parity.shared::cta.b64 p, [%0], %1;\n"
        "@p bra D;\n"
        "mov.u32 n, 0;\n"
        "W:\nmbarrier.try_wait.parity.shared::cta.b64 p, [%0], %1;\n"
        "@p bra D;\n"
        "add.u32 n, n, 1;\nsetp.lt.u32 p, n, 4194304;\n@p bra W;\ntrap;\n"
        "D:\n}" ::"r"(b), "r"(ph) : "memory");
}
__device__ __forceinline__ bool mbar_test(uint32_t b, uint32_t ph) {
    uint32_t r;
    asm volatile("{\n.reg .pred p;\nmbarrier.test_wait.parity.shared::cta.b64 p, [%1], %2;\nselp.u32 %0, 1, 0, p;\n}"
                 : "=r"(r) : "r"(b), "r"(ph) : "memory");
    return r != 0;
}
__device__ __forceinline__ void pfw(const CUtensorMap* m, int row, int cb) {
    asm volatile("cp.async.bulk.prefetch.tensor.4d.L2.global [%0, {%1, %1, %2, %3}];" ::"l"(m), "r"(0), "r"(cb), "r"(row >> 3) : "memory");
}
constexpr uint64_t POL_EF = 0x12F0000000000000ull;
__device__ __forceinline__ void tmaw(uint32_t dst, const CUtensorMap* m, int row, int cb, uint32_t bar) {
    asm volatile("cp.async.bulk.tensor.4d.shared::cluster.global.mbarrier::complete_tx::bytes [%0], [%1, {%3, %3, %4, %5}], [%2];"
                 ::"r"(dst), "l"(m), "r"(bar), "r"(0), "r"(cb), "r"(row >> 3) : "memory");
}
__device__ __forceinline__ void tma4_hint(uint32_t dst, const CUtensorMap* m, int c3, uint32_t bar, uint64_t pol) {
    asm volatile("cp.async.bulk.tensor.4d.shared::cluster.global.mbarrier::complete_tx::bytes.L2::cache_hint [%0], [%1, {%3, %3, %3, %4}], [%2], %5;"
                 ::"r"(dst), "l"(m), "r"(bar), "r"(0), "r"(c3), "l"(pol) : "memory");
}
__device__ __forceinline__ void tma2(uint32_t dst, const CUtensorMap* m, int c0, int c1, uint32_t bar) {
    asm volatile("cp.async.bulk.tensor.2d.shared::cluster.global.mbarrier::complete_tx::bytes [%0], [%1, {%3, %4}], [%2];"
                 ::"r"(dst), "l"(m), "r"(bar), "r"(c0), "r"(c1) : "memory");
}
__device__ __forceinline__ void bulk_g2s(uint32_t dst, const void* src, int bytes, uint32_t bar) {
    asm volatile("cp.async.bulk.shared::cluster.global.mbarrier::complete_tx::bytes [%0], [%1], %2, [%3];"
                 ::"r"(dst), "l"(src), "r"(bytes), "r"(bar) : "memory");
}
__device__ __forceinline__ void tma2_store(const CUtensorMap* m, uint32_t src, int c0, int c1) {
    asm volatile("cp.async.bulk.tensor.2d.global.shared::cta.bulk_group [%0, {%2, %3}], [%1];"
                 ::"l"(m), "r"(src), "r"(c0), "r"(c1) : "memory");
}
__device__ __forceinline__ void wg_fence() { asm volatile("wgmma.fence.sync.aligned;" ::: "memory"); }
__device__ __forceinline__ void wg_commit() { asm volatile("wgmma.commit_group.sync.aligned;" ::: "memory"); }
template <int N> __device__ __forceinline__ void wg_wait() { asm volatile("wgmma.wait_group.sync.aligned %0;" ::"n"(N) : "memory"); }
template <int N> __device__ __forceinline__ void acc_fence(float (&d)[N]) {
#pragma unroll
    for (int i = 0; i < N; i++) asm volatile("" : "+f"(d[i])::"memory");
}
template <uint32_t OFF> __device__ __forceinline__ void sts128i(uint32_t p, uint32_t a, uint32_t b, uint32_t c, uint32_t d) {
    asm volatile("st.shared.v4.u32 [%0+%5], {%1, %2, %3, %4};" ::"r"(p), "r"(a), "r"(b), "r"(c), "r"(d), "n"(OFF) : "memory");
}
template <uint32_t OFF> __device__ __forceinline__ void lds128i(uint32_t p, float* v) {
    asm volatile("ld.shared.v4.f32 {%0, %1, %2, %3}, [%4+%5];" : "=f"(v[0]), "=f"(v[1]), "=f"(v[2]), "=f"(v[3]) : "r"(p), "n"(OFF) : "memory");
}
template <uint32_t OFF> __device__ __forceinline__ void lds128u(uint32_t p, uint32_t* v) {
    asm volatile("ld.shared.v4.u32 {%0, %1, %2, %3}, [%4+%5];" : "=r"(v[0]), "=r"(v[1]), "=r"(v[2]), "=r"(v[3]) : "r"(p), "n"(OFF) : "memory");
}
#define SCHED_FENCE(cnt, k) do { if ((cnt) == prm.never + (int)(k)) { wg_wait<0>(); __trap(); } } while (0)
template <uint32_t LBO, uint32_t SBO, uint32_t SWZ>
__device__ __forceinline__ uint64_t mkdesc(uint32_t addr) {
    uint32_t lo = ((addr & 0x3FFFF) >> 4) | ((LBO >> 4) << 16);
    uint32_t hi = (SBO >> 4) | (SWZ << 30);
    return ((uint64_t)hi << 32) | lo;
}

template <int TA, int TB>
__device__ __forceinline__ void wgmma160(float (&d)[80], uint64_t da, uint64_t db, int scale_d) {
    asm volatile(
        "{\n.reg .pred p;\nsetp.ne.b32 p, %82, 0;\n"
        "wgmma.mma_async.sync.aligned.m64n160k16.f32.bf16.bf16 "
        "{%0, %1, %2, %3, %4, %5, %6, %7, %8, %9, %10, %11, %12, %13, %14, %15, %16, %17, %18, %19, "
        "%20, %21, %22, %23, %24, %25, %26, %27, %28, %29, %30, %31, %32, %33, %34, %35, %36, %37, %38, %39, "
        "%40, %41, %42, %43, %44, %45, %46, %47, %48, %49, %50, %51, %52, %53, %54, %55, %56, %57, %58, %59, "
        "%60, %61, %62, %63, %64, %65, %66, %67, %68, %69, %70, %71, %72, %73, %74, %75, %76, %77, %78, %79}, "
        "%80, %81, p, 1, 1, %83, %84;\n}\n"
        : "+f"(d[0]), "+f"(d[1]), "+f"(d[2]), "+f"(d[3]), "+f"(d[4]), "+f"(d[5]), "+f"(d[6]), "+f"(d[7]),
          "+f"(d[8]), "+f"(d[9]), "+f"(d[10]), "+f"(d[11]), "+f"(d[12]), "+f"(d[13]), "+f"(d[14]), "+f"(d[15]),
          "+f"(d[16]), "+f"(d[17]), "+f"(d[18]), "+f"(d[19]), "+f"(d[20]), "+f"(d[21]), "+f"(d[22]), "+f"(d[23]),
          "+f"(d[24]), "+f"(d[25]), "+f"(d[26]), "+f"(d[27]), "+f"(d[28]), "+f"(d[29]), "+f"(d[30]), "+f"(d[31]),
          "+f"(d[32]), "+f"(d[33]), "+f"(d[34]), "+f"(d[35]), "+f"(d[36]), "+f"(d[37]), "+f"(d[38]), "+f"(d[39]),
          "+f"(d[40]), "+f"(d[41]), "+f"(d[42]), "+f"(d[43]), "+f"(d[44]), "+f"(d[45]), "+f"(d[46]), "+f"(d[47]),
          "+f"(d[48]), "+f"(d[49]), "+f"(d[50]), "+f"(d[51]), "+f"(d[52]), "+f"(d[53]), "+f"(d[54]), "+f"(d[55]),
          "+f"(d[56]), "+f"(d[57]), "+f"(d[58]), "+f"(d[59]), "+f"(d[60]), "+f"(d[61]), "+f"(d[62]), "+f"(d[63]),
          "+f"(d[64]), "+f"(d[65]), "+f"(d[66]), "+f"(d[67]), "+f"(d[68]), "+f"(d[69]), "+f"(d[70]), "+f"(d[71]),
          "+f"(d[72]), "+f"(d[73]), "+f"(d[74]), "+f"(d[75]), "+f"(d[76]), "+f"(d[77]), "+f"(d[78]), "+f"(d[79])
        : "l"(da), "l"(db), "r"(scale_d), "n"(TA), "n"(TB));
}
template <int TA, int TB>
__device__ __forceinline__ void wgmma80(float (&d)[40], uint64_t da, uint64_t db, int scale_d) {
    asm volatile(
        "{\n.reg .pred p;\nsetp.ne.b32 p, %42, 0;\n"
        "wgmma.mma_async.sync.aligned.m64n80k16.f32.bf16.bf16 "
        "{%0, %1, %2, %3, %4, %5, %6, %7, %8, %9, %10, %11, %12, %13, %14, %15, %16, %17, %18, %19, "
        "%20, %21, %22, %23, %24, %25, %26, %27, %28, %29, %30, %31, %32, %33, %34, %35, %36, %37, %38, %39}, "
        "%40, %41, p, 1, 1, %43, %44;\n}\n"
        : "+f"(d[0]), "+f"(d[1]), "+f"(d[2]), "+f"(d[3]), "+f"(d[4]), "+f"(d[5]), "+f"(d[6]), "+f"(d[7]),
          "+f"(d[8]), "+f"(d[9]), "+f"(d[10]), "+f"(d[11]), "+f"(d[12]), "+f"(d[13]), "+f"(d[14]), "+f"(d[15]),
          "+f"(d[16]), "+f"(d[17]), "+f"(d[18]), "+f"(d[19]), "+f"(d[20]), "+f"(d[21]), "+f"(d[22]), "+f"(d[23]),
          "+f"(d[24]), "+f"(d[25]), "+f"(d[26]), "+f"(d[27]), "+f"(d[28]), "+f"(d[29]), "+f"(d[30]), "+f"(d[31]),
          "+f"(d[32]), "+f"(d[33]), "+f"(d[34]), "+f"(d[35]), "+f"(d[36]), "+f"(d[37]), "+f"(d[38]), "+f"(d[39])
        : "l"(da), "l"(db), "r"(scale_d), "n"(TA), "n"(TB));
}
__device__ __forceinline__ uint32_t pack_bf16(float lo, float hi) {
    uint32_t r;
    asm("cvt.rn.bf16x2.f32 %0, %1, %2;" : "=r"(r) : "f"(hi), "f"(lo));
    return r;
}
__device__ __forceinline__ uint32_t hadd2(uint32_t a, uint32_t b) {
    uint32_t r;
    asm("add.rn.bf16x2 %0, %1, %2;" : "=r"(r) : "r"(a), "r"(b));
    return r;
}
__device__ __forceinline__ void lsum(float& l, const uint32_t* w) {
    const uint32_t t = hadd2(hadd2(hadd2(w[0], w[1]), hadd2(w[2], w[3])), hadd2(hadd2(w[4], w[5]), hadd2(w[6], w[7])));
    l += __uint_as_float(t << 16) + __uint_as_float(t & 0xffff0000u);
}
__device__ __forceinline__ float ex2(float x) {
    float r;
    asm("ex2.approx.ftz.f32 %0, %1;" : "=f"(r) : "f"(x));
    return r;
}
__device__ __forceinline__ void stsm4t(uint32_t addr, uint32_t a, uint32_t b, uint32_t c, uint32_t d) {
    asm volatile("stmatrix.sync.aligned.m8n8.x4.trans.shared.b16 [%0], {%1, %2, %3, %4};"
                 ::"r"(addr), "r"(a), "r"(b), "r"(c), "r"(d) : "memory");
}
__device__ __forceinline__ void stg128(void* p, uint32_t a, uint32_t b, uint32_t c, uint32_t d) {
    asm volatile("st.global.v4.u32 [%0], {%1, %2, %3, %4};" ::"l"(p), "r"(a), "r"(b), "r"(c), "r"(d) : "memory");
}

template <int TB> struct PB;
template <> struct PB<0> { static constexpr uint32_t LBO = 16, STEP = 32; };
template <> struct PB<1> { static constexpr uint32_t LBO = 2048, STEP = 1024; };

template <int W, int TB, int cont = 1>
__device__ __forceinline__ void quad_shared(float (&a0)[80], float (&a1)[80], uint32_t par, bool leader, bool rel0 = true) {
    static_for<4>([&](auto I) {
        constexpr uint32_t i = I.value;
        constexpr uint32_t rel = sb + B_PREMPTY + 8 * ((i + 3) & 3);
        const uint64_t da = mkdesc<16, 2048, 1>(sb + i * PR_BYTES);
        const uint64_t db = mkdesc<PB<TB>::LBO, 512, 2>(sb + i * PR_BYTES + 8192);
        constexpr int acc = i == 0 ? cont : 1;
        const bool dorel = leader && (i != 0 || (cont && rel0));
        constexpr int W0 = W < 10 ? W : W / 1000, W1 = W < 10 ? W : W / 100 % 10, W2 = W < 10 ? W : W / 10 % 10, W3 = W % 10;
        constexpr int RP = W0 <= 1 ? 0 : (W1 <= 2 ? 1 : (W2 <= 3 ? 2 : 3));
        mbar_wait(sb + B_PRFULL + 8 * i, par);
        wg_wait<W0 - 1>();
        if (RP == 0 && dorel) mbar_arrive(rel);
        wg_fence();
        wgmma160<1, TB>(a0, da, db, acc);
        wg_commit();
        wg_wait<W1 - 1>();
        if (RP == 1 && dorel) mbar_arrive(rel);
        wgmma160<1, TB>(a1, da + (1024 >> 4), db, acc);
        wg_commit();
        wg_wait<W2 - 1>();
        if (RP == 2 && dorel) mbar_arrive(rel);
        wgmma160<1, TB>(a0, da + (4096 >> 4), db + (PB<TB>::STEP >> 4), 1);
        wg_commit();
        wg_wait<W3 - 1>();
        if (RP == 3 && dorel) mbar_arrive(rel);
        wgmma160<1, TB>(a1, da + (5120 >> 4), db + (PB<TB>::STEP >> 4), 1);
        wg_commit();
    });
}
__device__ __forceinline__ void quad_alone(float (&a0)[80], float (&a1)[80], uint32_t base, uint32_t par, uint32_t pbase,
                                           int cont, bool leader) {
    const uint64_t da0 = mkdesc<16, 2048, 1>(sb) + base * (PR_BYTES >> 4);
    const uint64_t db0 = mkdesc<16, 512, 2>(sb + 8192) + base * (PR_BYTES >> 4);
    static_for<4>([&](auto I) {
        constexpr uint32_t i = I.value;
        const uint64_t da = da0 + i * (PR_BYTES >> 4), db = db0 + i * (PR_BYTES >> 4);
        const int acc = i == 0 ? cont : 1;
        mbar_wait(sb + B_PRFULL + 8 * i + 8 * base, par);
        wg_fence();
        wgmma160<1, 0>(a0, da, db, acc);
        wgmma160<1, 0>(a1, da + (1024 >> 4), db, acc);
        wgmma160<1, 0>(a0, da + (4096 >> 4), db + (32 >> 4), 1);
        wgmma160<1, 0>(a1, da + (5120 >> 4), db + (32 >> 4), 1);
        wg_commit();
        wg_wait<2>();
        if (leader && (i >= 2 || cont)) mbar_arrive(sb + B_PREMPTY + 8 * ((i + 2) & 3) + 8 * (i < 2 ? pbase : base));
    });
}

constexpr float QSCALE = 0.08838834764831845f * 1.4426950408889634f;

__device__ __forceinline__ uint32_t packq(float a, float b) { return pack_bf16(a * QSCALE, b * QSCALE); }
__device__ __forceinline__ float rbf(float x) { return __uint_as_float(pack_bf16(x, 0.f) << 16); }

__device__ __noinline__ void slow_head(const __nv_bfloat16* xp, const __nv_bfloat16* wp, const __nv_bfloat16* kp,
                                       const __nv_bfloat16* vp, unsigned char* os, int warp, int lane) {
    for (int qn = warp; qn < SQ; qn += 4) {
        float q[4] = {0.f, 0.f, 0.f, 0.f}, o[4] = {0.f, 0.f, 0.f, 0.f};
#pragma unroll 8
        for (int k = 0; k < 1024; k++) {
            const float xv = __bfloat162float(xp[qn * 1024 + k]);
            const uint2 w = __ldg(reinterpret_cast<const uint2*>(wp + (size_t)k * 4096 + 4 * lane));
            q[0] += xv * __uint_as_float(w.x << 16);
            q[1] += xv * __uint_as_float(w.x & 0xffff0000u);
            q[2] += xv * __uint_as_float(w.y << 16);
            q[3] += xv * __uint_as_float(w.y & 0xffff0000u);
        }
#pragma unroll
        for (int u = 0; u < 4; u++) q[u] = rbf(q[u]);
        float m = -INFINITY, l = 0.f;
        for (int key = 0; key < SK; key += 4) {
            float s[4];
            uint2 vv[4];
#pragma unroll
            for (int u = 0; u < 4; u++) {
                const uint2 kk = __ldg(reinterpret_cast<const uint2*>(kp + (key + u) * 128 + 4 * lane));
                vv[u] = __ldg(reinterpret_cast<const uint2*>(vp + (key + u) * 128 + 4 * lane));
                s[u] = q[0] * __uint_as_float(kk.x << 16) + q[1] * __uint_as_float(kk.x & 0xffff0000u) +
                       q[2] * __uint_as_float(kk.y << 16) + q[3] * __uint_as_float(kk.y & 0xffff0000u);
            }
#pragma unroll
            for (int off = 16; off; off >>= 1) {
#pragma unroll
                for (int u = 0; u < 4; u++) s[u] += __shfl_xor_sync(0xffffffffu, s[u], off);
            }
#pragma unroll
            for (int u = 0; u < 4; u++) s[u] = rbf(rbf(s[u]) * 0.08838834764831845f) * 1.4426950408889634f;
            const float mn = fmaxf(fmaxf(m, fmaxf(s[0], s[1])), fmaxf(s[2], s[3]));
            const float mref = (mn == -INFINITY) ? 0.f : mn;
            const float corr = exp2f(m - mref);
            m = mn;
            l *= corr;
            o[0] *= corr; o[1] *= corr; o[2] *= corr; o[3] *= corr;
#pragma unroll
            for (int u = 0; u < 4; u++) {
                const float pw = exp2f(s[u] - mref);
                l += pw;
                o[0] += pw * __uint_as_float(vv[u].x << 16);
                o[1] += pw * __uint_as_float(vv[u].x & 0xffff0000u);
                o[2] += pw * __uint_as_float(vv[u].y << 16);
                o[3] += pw * __uint_as_float(vv[u].y & 0xffff0000u);
            }
        }
        const float inv = 1.f / l;
#pragma unroll
        for (int u = 0; u < 4; u++) {
            const int d = 4 * lane + u;
            unsigned short* a = reinterpret_cast<unsigned short*>(
                os + (d >> 5) * 10240 + (qn >> 5) * 2048 + (d & 31) * 64 + ((((qn & 31) >> 3) ^ ((d & 7) >> 1)) << 4) + (qn & 7) * 2);
            *a = (unsigned short)(pack_bf16(o[u] * inv, 0.f) & 0xffffu);
        }
    }
}

#define CTA_COORDS()                                   \
    int cta;                                           \
    asm volatile("mov.u32 %0, %ctaid.x;" : "=r"(cta)); \
    const int g = cta >> 3, j = cta & 7, br = cta >> 6, b = g & 7; \
    (void)g; (void)j; (void)br; (void)b

__global__ void __launch_bounds__(512, 1) mha_fused_kernel(const __grid_constant__ Params prm) {
    extern __shared__ __align__(1024) unsigned char smem_raw[];
    if ((uint32_t)__cvta_generic_to_shared(smem_raw) != sb) __trap();
    const int wg = __shfl_sync(0xffffffffu, threadIdx.x >> 7, 0);
    const int lane = threadIdx.x & 31;

    if (threadIdx.x < 96) {
        const int w = __shfl_sync(0xffffffffu, threadIdx.x >> 5, 0);
        if (elect_one()) {
            CTA_COORDS();
#pragma unroll
            for (int i = 0; i < 4; i++) mbar_init(sb + B_PRFULL + 32 * w + 8 * i, 1);
            asm volatile("fence.mbarrier_init.release.cluster;" ::: "memory");
            asm volatile("fence.proxy.async.shared::cta;" ::: "memory");
            if (w == 2) {
#pragma unroll 1
                for (int n = 0; n < 4; n++) {
                    const uint32_t s = 8 + n;
                    tmaw(sb + s * PR_BYTES, &prm.wq[br], n * 32, 2 * j, sb + B_PRFULL + 8 * s);
                    tma2(sb + s * PR_BYTES + 8192, &prm.x[br], n * 32, b * SQ, sb + B_PRFULL + 8 * s);
                    mbar_expect(sb + B_PRFULL + 8 * s, PR_BYTES);
                }
            }
        }
        __syncwarp();
    } else if (threadIdx.x >= 128 && lane < 8) {
        const uint32_t a = SM_BAR + 8 * ((threadIdx.x >> 5) - 4 + 12 * lane);
        const bool one = a < B_KEMPTY || (a >= B_VFULL && a < B_VEMPTY) || (a >= B_QFULL && a < B_QREADY) ||
                         (a >= B_QVIS && a < B_PREMPTY) || (a >= B_ORDY && a < B_KVGO);
        if (a < B_PRFULL || a >= B_PREMPTY) mbar_init(sb + a, one ? 1 : 4);
        asm volatile("fence.mbarrier_init.release.cluster;" ::: "memory");
        asm volatile("fence.proxy.async.shared::cta;" ::: "memory");
    }
    __syncthreads();

    if (wg == 0) {
        asm volatile("setmaxnreg.dec.sync.aligned.u32 24;");
        const int warp = __shfl_sync(0xffffffffu, warp_now(), 0);
        if (warp == 0) {
            if (elect_one()) {
                CTA_COORDS();
                const int row0 = (b * NH + j) * SK;
                mbar_wait(sb + B_KVGO, 0);
#pragma unroll 1
                for (int t = 0; t < 65; t++) {
                    if (t < 64) {
                        const uint32_t s = t & 1;
                        const bool newq = (t & 15) == 1 && t > 1;
                        const unsigned char* qsrc = g_scr + (size_t)(g * 32 + ((t >> 4) - 1) * 8 + j) * 40960;
                        if (newq) {
                            mbar_wait(sb + B_QVIS + 8 * (t >> 4), 0);
                            mbar_wait(sb + B_QFREE, ((t >> 4) & 1) ^ 1);
                            mbar_expect(sb + B_QFULL, 20480);
                            bulk_g2s(sb + SM_Q, qsrc, 20480, sb + B_QFULL);
                        }
                        mbar_wait(sb + B_KEMPTY + 8 * s, ((t >> 1) & 1) ^ 1);
                        if (newq) {
                            mbar_expect(sb + B_QFULL + 8, 20480);
                            bulk_g2s(sb + SM_Q + 20480, qsrc + 20480, 20480, sb + B_QFULL + 8);
                        }
                        mbar_expect(sb + B_KFULL + 8 * s, 16384);
                        tma4_hint(sb + SM_K + s * 16384, &prm.k[br], (row0 + (t >> 4) * (8 * SK) + (t & 15) * 64) >> 3,
                                  sb + B_KFULL + 8 * s, POL_EF);
                    }
#pragma unroll 1
                    for (int u = t == 2 ? 2 : t - 1; u >= 0 && u < (t == 1 ? 2 : t); u++) {
                        const uint32_t s = u & 1;
                        mbar_wait(sb + B_VEMPTY + 8 * s, ((u >> 1) & 1) ^ 1);
                        mbar_expect(sb + B_VFULL + 8 * s, 16384);
                        tma4_hint(sb + SM_V + s * 16384, &prm.v[br], (row0 + (u >> 4) * (8 * SK) + (u & 15) * 64) >> 3,
                                  sb + B_VFULL + 8 * s, POL_EF);
                    }
                }
            }
        } else if (warp == 1) {
            if (lane == 0) {
                CTA_COORDS();
                const unsigned int target = g_epoch[cta] + 1;
#pragma unroll 1
                for (int r = 0; r < 4; r++) {
                    mbar_wait(sb + B_ODONE + 8 * r, 0);
                    asm volatile("st.release.gpu.global.u32 [%0], %1;" ::"l"(g_flag + g * 32 + r * 8 + j), "r"(target) : "memory");
                }
            }
        } else if (warp == 2) {
            if (elect_one()) {
                CTA_COORDS();
                int pf = 8 + (b >> 2);
#pragma unroll 1
                for (int n = 4; n < 12; n++) {
                    const uint32_t s = (8 - (n & 12)) + (n & 3);
                    mbar_expect(sb + B_PRFULL + 8 * s, PR_BYTES);
                    tmaw(sb + s * PR_BYTES, &prm.wq[br], n * 32, 2 * j, sb + B_PRFULL + 8 * s);
                    tma2(sb + s * PR_BYTES + 8192, &prm.x[br], n * 32, b * SQ, sb + B_PRFULL + 8 * s);
                }
                auto load_q = [&](int q, uint32_t base, uint32_t par) {
                    const uint32_t dst = sb + base * PR_BYTES, bar = sb + B_PRFULL + 8 * base;
                    const int k0 = (q & 7) * 128, hc = 2 * ((q >> 3) * 8 + j);
#pragma unroll
                    for (int i = 0; i < 4; i++) {
                        mbar_wait(bar + (B_PREMPTY - B_PRFULL) + 8 * i, par ^ 1);
                        tma2(dst + i * PR_BYTES + 8192, &prm.x[br], k0 + i * 32, b * SQ, bar + 8 * i);
                        tmaw(dst + i * PR_BYTES, &prm.wq[br], k0 + i * 32, hc, bar + 8 * i);
                        mbar_expect(bar + 8 * i, PR_BYTES);
                    }
                    const int mend = q <= 8 ? 8 + HP * (q - 2) : q + PDQ + 1;
#pragma unroll 1
                    for (; pf < mend; pf += 2) {
                        if (pf < 32) pfw(&prm.wq[br], (pf & 7) * 128 + (b & 3) * 32, 2 * ((pf >> 3) * 8 + j));
                        else pfw(&prm.wo[br], (pf - 32) * 128 + (b & 3) * 32, 2 * j);
                    }
                };
#pragma unroll 1
                for (int q = 3; q < 8; q++) load_q(q, 4 * (q & 1), ((q - 1) >> 1) & 1);
#pragma unroll 1
                for (int q = 8; q < 32; q++) load_q(q, 0, (q + 1) & 1);
                const unsigned char* osrc = g_scr + (size_t)g * (128 * 10240);
                auto load_o = [&](int q, auto BASE) {
                    constexpr uint32_t dst = sb + BASE.value * PR_BYTES, bar = sb + B_PRFULL + 8 * BASE.value;
                    mbar_wait(sb + B_ORDY + 8 * q, 0);
                    uint32_t hh;
                    asm volatile("ld.shared.u8 %0, [%1];" : "=r"(hh) : "r"(sb + SM_ORD + q) : "memory");
#pragma unroll
                    for (int i = 0; i < 4; i++) {
                        if (BASE.value == 0) mbar_wait(sb + B_PREMPTY + 8 * i, q & 1);
                        else mbar_wait(sb + B_PRFULL + 8 * i, 1);
                        tmaw(dst + i * PR_BYTES, &prm.wo[br], hh * 128 + i * 32, 2 * j, bar + 8 * i);
                        bulk_g2s(dst + i * PR_BYTES + 8192, osrc + hh * 40960 + i * 10240, 10240, bar + 8 * i);
                        mbar_expect(bar + 8 * i, PR_BYTES);
                    }
                };
#pragma unroll 1
                for (int q = 0; q < 31; q++) {
                    load_o(q, IC<0>{});
                    const int m = q + PDQ;
                    if (m < 24 && (m & 1) == (b >> 2)) pfw(&prm.wo[br], m * 128 + (b & 3) * 32, 2 * j);
                }
                load_o(31, IC<8>{});
            }
        } else {
            CTA_COORDS();
            const unsigned int target = g_epoch[cta] + 1;
            if (lane == 0) {
#pragma unroll 1
                for (int r = 1; r < 4; r++) {
                    mbar_wait_lim(sb + B_QREADY + 8 * r, 0);
                    asm volatile("fence.acq_rel.gpu;" ::: "memory");
                    asm volatile("fence.proxy.async.global;" ::: "memory");
                    mbar_arrive(sb + B_QVIS + 8 * r);
                    if (r == 2) break;
                }
            }
            __syncwarp();
            int nr = 0;
            unsigned int seen = 0;
            bool q3 = false;
            unsigned int it = 0;
            while (nr < 32) {
                if (!q3 && mbar_test(sb + B_QREADY + 24, 0)) {
                    if (lane == 0) {
                        asm volatile("fence.acq_rel.gpu;" ::: "memory");
                        asm volatile("fence.proxy.async.global;" ::: "memory");
                        mbar_arrive(sb + B_QVIS + 24);
                    }
                    q3 = true;
                }
                unsigned int v;
                asm volatile("ld.acquire.gpu.global.u32 %0, [%1];" : "=r"(v) : "l"(g_flag + g * 32 + lane) : "memory");
                unsigned int fresh = __ballot_sync(0xffffffffu, v == target);
                fresh &= ~seen;
                if (fresh) {
                    asm volatile("fence.proxy.async.global;" ::: "memory");
                    if ((fresh >> lane) & 1) {
                        const uint32_t pos = nr + __popc(fresh & ((1u << lane) - 1));
                        asm volatile("st.shared.u8 [%0], %1;" ::"r"(sb + SM_ORD + pos), "r"(lane) : "memory");
                        mbar_arrive(sb + B_ORDY + 8 * pos);
                    }
                    nr += __popc(fresh);
                    seen |= fresh;
                }
                if (nr < 24) __nanosleep(400);
                else if (!mbar_test(sb + B_ADONE, 0)) __nanosleep(150);
                if (++it > 8388608u) __trap();
                __syncwarp();
            }
            if (lane == 0) g_epoch[cta] = target;
            mbar_wait_lim(sb + B_END, 0);
        }
    } else if (wg == 1) {
        asm volatile("setmaxnreg.dec.sync.aligned.u32 104;");
        float s[40], x[40];
#pragma unroll
        for (int i = 0; i < 40; i++) s[i] = x[i] = 0.f;
        const uint32_t t8 = lane & 7, m = lane >> 3;
        const uint32_t pst = sb + SM_P + (8 * (m >> 1) + t8) * 128 + (((2 * warp_now() + (m & 1)) ^ t8) << 4);
        auto qk = [&](uint32_t sl, int hf) {
            const uint64_t da = mkdesc<16, 2048, 1>(sb + SM_K + sl * 16384);
            const uint64_t db = mkdesc<4096, 256, 3>(sb + SM_Q + hf * 20480);
            wg_fence();
#pragma unroll
            for (int kk = 0; kk < 8; kk++)
                wgmma80<0, 1>(s, da + (((kk >> 2) * 1024 + (kk & 3) * 32) >> 4), db + ((kk * 512) >> 4), kk != 0 ? 1 : prm.zero);
            wg_commit();
        };
        auto stage = [&](int dir) {
            wg_wait<0>();
            acc_fence(s);
#pragma unroll
            for (int i = 0; i < 40; i++) x[i] = i < dir ? ex2(s[i]) : s[i] * prm.one;
            acc_fence(x);
        };
        auto expo = [&](uint32_t pa, int jj, int dir) {
            auto e = [&](int i) { return i < dir ? x[i] : ex2(x[i]); };
            stsm4t(pa + jj * 2048, pack_bf16(e(8 * jj), e(8 * jj + 1)), pack_bf16(e(8 * jj + 2), e(8 * jj + 3)),
                   pack_bf16(e(8 * jj + 4), e(8 * jj + 5)), pack_bf16(e(8 * jj + 6), e(8 * jj + 7)));
        };
        mbar_wait(sb + B_QREADY, 0);
        mbar_wait(sb + B_KFULL, 0);
        qk(0, 0);
#pragma unroll 1
        for (int t2 = 0; t2 < 32; t2++) {
            const uint32_t ph = t2 & 1;
            static_for<2>([&](auto SL) {
                constexpr uint32_t sl = SL.value;
                const uint32_t pa = pst + sl * P_BYTES;
                const bool last = sl == 1 && (t2 & 7) == 7;
                if (last) {
                    wg_wait<0>();
                    mbar_arrive_warp(sb + B_QFREE);
                }
                stage(DIRA);
                if (sl == 0 && (t2 & 7) == 0 && t2 != 0) mbar_wait(sb + B_QFULL + 8, ((t2 >> 3) & 1) ^ 1);
                qk(sl, 1);
                mbar_wait(sb + B_PEMPTY + 8 * sl, ph ^ 1);
                SCHED_FENCE(t2, 1 + sl);
#pragma unroll
                for (int jj = 0; jj < 5; jj++) expo(pa, jj, DIRA);
                wg_wait<0>();
                mbar_arrive_warp(sb + B_KEMPTY + 8 * sl);
                stage(DIRB);
#pragma unroll
                for (int jj = 0; jj < DIRB / 8; jj++) expo(pa + 10240, jj, DIRB);
                if (!last) {
                    mbar_wait_lim(sb + B_KFULL + 8 * (sl ^ 1), sl == 0 ? ph : ph ^ 1);
                    qk(sl ^ 1, 0);
                    if (sl == 0) SCHED_FENCE(t2, 0);
                }
#pragma unroll
                for (int jj = DIRB / 8; jj < 5; jj++) expo(pa + 10240, jj, DIRB);
                asm volatile("fence.acq_rel.cta;" ::: "memory");
                __syncwarp();
                mbar_arrive_warp(sb + B_PFULL + 8 * sl);
                if (last && t2 != 31) {
                    mbar_wait(sb + B_QFULL, (t2 >> 3) & 1);
                    mbar_wait(sb + B_KFULL, ph ^ 1);
                    qk(0, 0);
                }
            });
        }
        wg_wait<0>();
    } else if (wg == 2) {
        asm volatile("setmaxnreg.inc.sync.aligned.u32 192;");
        float o0[80], o1[80];
        const uint32_t prow = warp_now() * 8 + (lane >> 2);
        const uint32_t pld = prow * 128 + (((lane & 3) | ((prow & 1) << 2)) << 4);
#pragma unroll 1
        for (int r = 0; r < 4; r++) {
            float l[5] = {0.f, 0.f, 0.f, 0.f, 0.f};
            bool bad = false;
            auto pv_begin = [&](auto SL, auto ACC, uint32_t ph) {
                constexpr uint32_t sl = SL.value;
                mbar_wait(sb + B_VFULL + 8 * sl, ph);
                mbar_wait(sb + B_PFULL + 8 * sl, ph);
                asm volatile("fence.proxy.async.shared::cta;" ::: "memory");
                wg_fence();
                wgmma160<1, 0>(o0, mkdesc<16, 2048, 1>(sb + SM_V + sl * 16384), mkdesc<16, 1024, 1>(sb + SM_P + sl * P_BYTES), ACC.value);
                wg_commit();
                wgmma160<1, 0>(o1, mkdesc<16, 2048, 1>(sb + SM_V + sl * 16384 + 1024), mkdesc<16, 1024, 1>(sb + SM_P + sl * P_BYTES), ACC.value);
                wg_commit();
            };
            pv_begin(IC<0>{}, IC<0>{}, 0);
#pragma unroll 1
            for (int i2 = 0; i2 < 8; i2++) static_for<2>([&](auto SL) {
                constexpr uint32_t sl = SL.value;
                const uint64_t da = mkdesc<16, 2048, 1>(sb + SM_V + sl * 16384);
                const uint64_t db = mkdesc<16, 1024, 1>(sb + SM_P + sl * P_BYTES);
                if (sl == 0) wg_fence();
                uint32_t w[8];
                static_for<8, 2>([&](auto K) {
                    constexpr int k = K.value;
                    if constexpr (k >= PVW) wg_wait<PVW - 1>();
                    if constexpr (k >= 3) wg_fence();
                    if (k & 1) wgmma160<1, 0>(o1, da + ((1024 + (k >> 1) * 4096) >> 4), db + (((k >> 1) * 32) >> 4), 1);
                    else wgmma160<1, 0>(o0, da + (((k >> 1) * 4096) >> 4), db + (((k >> 1) * 32) >> 4), 1);
                    wg_commit();
                    if constexpr (k >= 3) lsum(l[k - 3], w);
                    if constexpr (k < 7) {
                        lds128u<sb + SM_P + sl * P_BYTES + (k - 2) * 4096>(pld, w);
                        lds128u<sb + SM_P + sl * P_BYTES + (k - 2) * 4096>(pld ^ 64, w + 4);
                        SCHED_FENCE(i2, k + 8 * sl);
                    }
                });
                if (sl == 1 && i2 == 7) {
#pragma unroll
                    for (int k = 0; k < 5; k++) l[k] += __shfl_xor_sync(0xffffffffu, l[k], 1);
#pragma unroll
                    for (int k = 0; k < 5; k++) l[k] += __shfl_xor_sync(0xffffffffu, l[k], 2);
                    const uint32_t ln = lane_now();
                    const uint32_t la = sb + SM_LINV + (((ln >> 3) & 3) * 8 + warp_now() * 2 + ((ln >> 2) & 1)) * 4;
#pragma unroll
                    for (int k = 0; k < 5; k++) {
                        bad |= !(l[k] >= 0.00390625f && l[k] <= 4294967296.f);
                        float v;
                        asm("rcp.approx.ftz.f32 %0, %1;" : "=f"(v) : "f"(l[k]));
                        if ((ln & 3) == 0) asm volatile("st.shared.f32 [%0], %1;" ::"r"(la + 128 * k), "f"(v) : "memory");
                    }
                }
                wg_wait<0>();
                __syncwarp();
                mbar_arrive_warp(sb + B_VEMPTY + 8 * sl);
                mbar_arrive_warp(sb + B_PEMPTY + 8 * sl);
                if (sl == 0) pv_begin(IC<1>{}, IC<1>{}, i2 & 1);
                else if (i2 != 7) pv_begin(IC<0>{}, IC<1>{}, (i2 & 1) ^ 1);
            });
            wg_wait<0>();
            if (r == 3) mbar_arrive_warp(sb + B_ADONE);
            acc_fence(o0);
            acc_fence(o1);
            uint32_t redo;
            asm volatile("{\n.reg .pred p, q;\nsetp.ne.u32 p, %1, 0;\nbar.red.or.pred q, 1, 128, p;\nselp.u32 %0, 1, 0, q;\n}"
                         : "=r"(redo) : "r"((uint32_t)bad) : "memory");
            if (r < 3) mbar_wait(sb + B_QFULL, r & 1);
            CTA_COORDS();
            unsigned char* os = g_scr + (size_t)(g * 32 + 8 * r + j) * 40960;
            if (__any_sync(0xffffffffu, redo)) {
                const int h = 8 * r + j;
                if (r < 3) mbar_wait(sb + B_QFULL + 8, r & 1);
                slow_head(prm.xp[br] + (size_t)b * SQ * 1024, prm.wqp[br] + h * 128, prm.kp[br] + (size_t)(b * NH + h) * SK * 128,
                          prm.vp[br] + (size_t)(b * NH + h) * SK * 128, os, warp_now(), lane_now());
            } else {
                const uint32_t ln = lane_now(), g8 = ln >> 2, warp = warp_now();
                unsigned char* op = os + (warp >> 1) * 10240 + (16 * (warp & 1) + g8) * 64 + (((ln & 3) ^ (g8 >> 1)) << 4);
                const uint32_t li = (ln & 3) * 32;
                float iv[40];
                lds128i<sb + SM_LINV>(li, iv);
                lds128i<sb + SM_LINV + 16>(li, iv + 4);
                auto put = [&](const float* o, const float* v, unsigned char* p) {
                    stg128(p, pack_bf16(o[0] * v[0], o[1] * v[1]), pack_bf16(o[4] * v[2], o[5] * v[3]),
                           pack_bf16(o[8] * v[4], o[9] * v[5]), pack_bf16(o[12] * v[6], o[13] * v[7]));
                };
                static_for<5>([&](auto I) {
                    constexpr int i = I.value;
                    if constexpr (i < 4) {
                        lds128i<sb + SM_LINV + 128 * (i + 1)>(li, iv + 8 * (i + 1));
                        lds128i<sb + SM_LINV + 128 * (i + 1) + 16>(li, iv + 8 * (i + 1) + 4);
                    }
                    put(o0 + 16 * i, iv + 8 * i, op + i * 2048);
                    put(o0 + 16 * i + 2, iv + 8 * i, op + i * 2048 + 512);
                });
                if (r < 3) mbar_wait(sb + B_QFULL + 8, r & 1);
                static_for<5>([&](auto I) {
                    constexpr int i = I.value;
                    put(o1 + 16 * i, iv + 8 * i, op + 20480 + i * 2048);
                    put(o1 + 16 * i + 2, iv + 8 * i, op + 20480 + i * 2048 + 512);
                });
            }
            __syncwarp();
            mbar_arrive_warp(sb + B_ODONE + 8 * r);
        }
    } else {
        asm volatile("setmaxnreg.inc.sync.aligned.u32 192;");
        float a0[80], a1[80];
        const bool leader = lane == 0;
        {
            uint32_t pbase = 0;
#pragma unroll 1
            for (int q = 0; q < 8; q++) {
                const uint32_t base = q == 0 ? 8 : 4 * (q & 1), par = q == 0 ? 0 : ((q - 1) >> 1) & 1;
                if (leader && q == KV_START) mbar_arrive(sb + B_KVGO);
                quad_alone(a0, a1, base, par, pbase, q, leader);
                pbase = base;
            }
            const uint32_t ln = lane_now(), g8 = ln >> 2;
            const uint32_t qo = ((ln >> 1) & 1) * 4096 + (16 * warp_now() + g8) * 32 + (((ln & 1) ^ (g8 >> 2)) << 4);
            wg_wait<0>();
            acc_fence(a0);
            acc_fence(a1);
            asm volatile("bar.sync 2, 128;" ::: "memory");
            static_for<20>([&](auto I) {
                constexpr int i = I.value, a = 16 * (i >> 2) + 2 * (i & 1);
                const float* v = (i & 2) ? a1 : a0;
                sts128i<sb + SM_Q + (i >> 2) * 8192 + ((i >> 1) & 1) * 2048 + (i & 1) * 256>(
                    qo, packq(v[a], v[a + 1]), packq(v[a + 4], v[a + 5]), packq(v[a + 8], v[a + 9]), packq(v[a + 12], v[a + 13]));
            });
            asm volatile("fence.proxy.async.shared::cta;" ::: "memory");
            __syncwarp();
            mbar_arrive_warp(sb + B_QREADY);
        }
#pragma unroll 1
        for (int r = 1; r < 4; r++) {
            quad_shared<PWQ, 0, 0>(a0, a1, 1, leader);
#pragma unroll 1
            for (int q = 1; q < 8; q++) {
                quad_shared<PWQ, 0>(a0, a1, (q + 1) & 1, leader);
            }
            CTA_COORDS();
            const uint32_t ln = lane_now(), g8 = ln >> 2;
            unsigned char* qp = g_scr + (size_t)(g * 32 + (r - 1) * 8 + j) * 40960 + ((ln >> 1) & 1) * 4096 +
                                (16 * warp_now() + g8) * 32 + (((ln & 1) ^ (g8 >> 2)) << 4);
            wg_wait<0>();
            acc_fence(a0);
            acc_fence(a1);
            mbar_arrive_warp(sb + B_PREMPTY + 8 * 3);
#pragma unroll
            for (int i = 0; i < 20; i++) {
                const int a = 16 * (i >> 2) + 2 * (i & 1);
                const float* v = (i & 2) ? a1 : a0;
                stg128(qp + (i >> 2) * 8192 + ((i >> 1) & 1) * 2048 + (i & 1) * 256, packq(v[a], v[a + 1]),
                       packq(v[a + 4], v[a + 5]), packq(v[a + 8], v[a + 9]), packq(v[a + 12], v[a + 13]));
            }
            __syncwarp();
            mbar_arrive_warp(sb + B_QREADY + 8 * r);
        }
        bool alone = false;
        quad_shared<PWO, 1, 0>(a0, a1, 1, leader);
#pragma unroll 1
        for (int q = 33; q < 63; q++) {
            const bool rel0 = q < 48 || mbar_test(sb + B_ORDY + 8 * (q - 32), 0);
            if (!rel0) {
                wg_wait<0>();
                if (leader) mbar_arrive(sb + B_PREMPTY + 8 * 3);
            }
            if (!alone && q >= 48) {
                mbar_wait(sb + B_PRFULL, (q + 1) & 1);
                uint32_t a;
                asm volatile("{\n.reg .pred p, q;\nmbarrier.test_wait.parity.shared::cta.b64 p, [%1], 0;\n"
                             "bar.red.and.pred q, 2, 128, p;\nselp.u32 %0, 1, 0, q;\n}" : "=r"(a) : "r"(sb + B_ADONE) : "memory");
                alone = a != 0;
            }
            if (alone) quad_shared<PWT, 1>(a0, a1, (q + 1) & 1, leader, rel0);
            else quad_shared<PWO, 1>(a0, a1, (q + 1) & 1, leader, rel0);
        }
        const uint32_t ln = lane_now(), t8 = ln & 7, m = ln >> 3, warp = __shfl_sync(0xffffffffu, warp_now(), 0);
        const uint32_t pst = sb + SM_Q + (8 * (m >> 1) + t8) * 128 + (((2 * warp + (m & 1)) ^ t8) << 4);
        static_for<4>([&](auto I) {
            constexpr uint32_t a = sb + (8 + I.value) * PR_BYTES;
            mbar_wait(sb + B_PRFULL + 8 * (8 + I.value), 1);
            wg_fence();
            wgmma160<1, 1>(a0, mkdesc<16, 2048, 1>(a), mkdesc<2048, 512, 2>(a + 8192), 1);
            wgmma160<1, 1>(a0, mkdesc<16, 2048, 1>(a + 4096), mkdesc<2048, 512, 2>(a + 9216), 1);
            wg_commit();
        });
        static_for<4>([&](auto I) {
            constexpr uint32_t a = sb + (8 + I.value) * PR_BYTES;
            wgmma160<1, 1>(a1, mkdesc<16, 2048, 1>(a + 1024), mkdesc<2048, 512, 2>(a + 8192), 1);
            wgmma160<1, 1>(a1, mkdesc<16, 2048, 1>(a + 5120), mkdesc<2048, 512, 2>(a + 9216), 1);
        });
        wg_commit();
        auto put_half = [&](const float (&a)[80], auto H) {
            static_for<OCH>([&](auto C) {
                constexpr int c = C.value, per = 10 / OCH;
#pragma unroll
                for (int jj = c * per; jj < (c + 1) * per; jj++)
                    stsm4t(pst + H.value * P_BYTES + jj * 2048, pack_bf16(a[8 * jj], a[8 * jj + 1]), pack_bf16(a[8 * jj + 2], a[8 * jj + 3]),
                           pack_bf16(a[8 * jj + 4], a[8 * jj + 5]), pack_bf16(a[8 * jj + 6], a[8 * jj + 7]));
                asm volatile("fence.proxy.async.shared::cta;" ::: "memory");
                if (warp == (c & 3)) {
                    asm volatile("bar.sync %0, 128;" ::"n"(3 + (H.value * OCH + c) % 10) : "memory");
                    if (elect_one()) {
                        CTA_COORDS();
                        tma2_store(&prm.out, sb + SM_Q + H.value * P_BYTES + c * per * 2048, br * 1024 + j * 128 + H.value * 64,
                                   b * SQ + c * per * 16);
                        asm volatile("cp.async.bulk.commit_group;" ::: "memory");
                    }
                    __syncwarp();
                } else {
                    asm volatile("bar.arrive %0, 128;" ::"n"(3 + (H.value * OCH + c) % 10) : "memory");
                }
            });
        };
        wg_wait<1>();
        acc_fence(a0);
        put_half(a0, IC<0>{});
        wg_wait<0>();
        acc_fence(a1);
        mbar_arrive_warp(sb + B_END);
        put_half(a1, IC<1>{});
        asm volatile("cp.async.bulk.wait_group 0;" ::: "memory");
    }
}

typedef CUresult (*EncodeFn)(CUtensorMap*, CUtensorMapDataType, cuuint32_t, void*, const cuuint64_t*, const cuuint64_t*,
                             const cuuint32_t*, const cuuint32_t*, CUtensorMapInterleave, CUtensorMapSwizzle,
                             CUtensorMapL2promotion, CUtensorMapFloatOOBfill);

void encode(EncodeFn fn, CUtensorMap* m, void* p, int rank, const cuuint64_t* dims, const cuuint64_t* strides,
            const cuuint32_t* box, CUtensorMapSwizzle swz) {
    cuuint32_t es[4] = {1, 1, 1, 1};
    fn(m, CU_TENSOR_MAP_DATA_TYPE_BFLOAT16, rank, p, dims, strides, box, es, CU_TENSOR_MAP_INTERLEAVE_NONE, swz,
       CU_TENSOR_MAP_L2_PROMOTION_L2_128B, CU_TENSOR_MAP_FLOAT_OOB_FILL_NONE);
}

}


extern "C" void kernel_launch(void* const* d_in, const int* in_sizes, int n_in, void* d_out, int out_size) {
    static EncodeFn fn = nullptr;
    if (!fn) {
        void* f = nullptr;
        cudaDriverEntryPointQueryResult st;
        cudaGetDriverEntryPoint("cuTensorMapEncodeTiled", &f, cudaEnableDefault, &st);
        fn = (EncodeFn)f;
        cudaFuncSetAttribute(mha_fused_kernel, cudaFuncAttributeMaxDynamicSharedMemorySize, SM_TOTAL);
    }
    Params prm;
    prm.zero = 0;
    prm.one = 1.f;
    prm.never = 1 << 20;
    for (int br = 0; br < 2; br++) {
        void* x = d_in[5 * br + 0];
        void* k = d_in[5 * br + 1];
        void* v = d_in[5 * br + 2];
        void* wq = d_in[5 * br + 3];
        void* wo = d_in[5 * br + 4];
        {
            cuuint64_t dims[4] = {64, 8, 2, (cuuint64_t)NH * SK}, str[3] = {256, 128, 2048};
            cuuint32_t box[4] = {64, 8, 2, 8};
            encode(fn, &prm.k[br], k, 4, dims, str, box, CU_TENSOR_MAP_SWIZZLE_128B);
            encode(fn, &prm.v[br], v, 4, dims, str, box, CU_TENSOR_MAP_SWIZZLE_128B);
        }
        {
            cuuint64_t dims[4] = {64, 8, 64, 128}, str[3] = {8192, 128, 65536};
            cuuint32_t box[4] = {64, 8, 2, 4};
            encode(fn, &prm.wq[br], wq, 4, dims, str, box, CU_TENSOR_MAP_SWIZZLE_128B);
        }
        {
            cuuint64_t dims[4] = {64, 8, 16, 512}, str[3] = {2048, 128, 16384};
            cuuint32_t box[4] = {64, 8, 2, 4};
            encode(fn, &prm.wo[br], wo, 4, dims, str, box, CU_TENSOR_MAP_SWIZZLE_128B);
        }
        {
            cuuint64_t dims[2] = {1024, 1280}, str[1] = {2048};
            cuuint32_t box[2] = {32, 160};
            encode(fn, &prm.x[br], x, 2, dims, str, box, CU_TENSOR_MAP_SWIZZLE_64B);
        }
        prm.kp[br] = (const __nv_bfloat16*)k;
        prm.vp[br] = (const __nv_bfloat16*)v;
        prm.xp[br] = (const __nv_bfloat16*)x;
        prm.wqp[br] = (const __nv_bfloat16*)wq;
    }
    {
        cuuint64_t dims[2] = {2048, 1280}, str[1] = {4096};
        cuuint32_t box[2] = {64, 160 / OCH};
        encode(fn, &prm.out, d_out, 2, dims, str, box, CU_TENSOR_MAP_SWIZZLE_128B);
    }
    mha_fused_kernel<<<NCTA, 512, SM_TOTAL, cudaStreamPerThread>>>(prm);
}
```
